```python
import torch

def _softmax(x, axis=-1):
    return torch.softmax(x, dim=axis)
def _gelu(x):
    return torch.nn.functional.gelu(x, approximate="tanh")
def _silu(x):
    return torch.nn.functional.silu(x)
def _sigmoid(x):
    return torch.sigmoid(x)
def _layernorm(x, axis=-1, eps=1e-5):
    m = x.mean(dim=axis, keepdim=True)
    v = x.var(dim=axis, keepdim=True, unbiased=False)
    return (x - m) / torch.sqrt(v + eps)
def _scatter_add(tgt, idx, src, axis=0):
    return tgt.clone().index_add_(axis, idx, src)
def _segment_sum(src, seg, n):
    out = torch.zeros((n,) + src.shape[1:], dtype=src.dtype)
    return out.index_add_(0, seg, src)
def _pad(x, pw):
    flat = tuple(v for pair in reversed(pw) for v in pair)
    return torch.nn.functional.pad(x, flat)

kernel_name = 'gated_mix__sliding_local_dilated__moe_arch_mod__prompt'

def setup_inputs():

    _w = (lambda a: (lambda t: t.to(torch.bfloat16) if t.is_floating_point() else t)(torch.as_tensor(a)))
    def _A_setup():
        B, S, D = 1, 2048, 640
        return {
            "x": _w((lambda *s: torch.randn(*s, dtype=torch.bfloat16) * 0.05)(B, S, D)),
            "wqkv": _w((lambda *s: torch.randn(*s, dtype=torch.bfloat16) * 0.8)(D, 3 * D)),
            "wo": _w((lambda *s: torch.randn(*s, dtype=torch.bfloat16) * 0.05)(D, D)),
        }
    _A_in = _A_setup()

    def _B_setup():
        B, S, D, F, C = 1, 2048, 640, 1728, 2
        return {
            "x": _w((lambda *s: torch.randn(*s, dtype=torch.bfloat16) * 0.05)(B, S, D)),
            "w_r": _w((lambda *s: torch.randn(*s, dtype=torch.bfloat16) * 1.6)(D)),
            "w_gate": _w((lambda *s: torch.randn(*s, dtype=torch.bfloat16) * 0.4)(D, F)),
            "w_up": _w((lambda *s: torch.randn(*s, dtype=torch.bfloat16) * 0.4)(D, F)),
            "w_down": _w((lambda *s: torch.randn(*s, dtype=torch.bfloat16) * 0.4)(F, D)),
        }
    _B_in = _B_setup()

    return {
        "A_x": _A_in["x"],
        "A_wqkv": _A_in["wqkv"],
        "A_wo": _A_in["wo"],
        "B_x": _B_in["x"],
        "B_w_r": _B_in["w_r"],
        "B_w_gate": _B_in["w_gate"],
        "B_w_up": _B_in["w_up"],
        "B_w_down": _B_in["w_down"],
        "gate_w": _w((lambda *s: torch.randn(*s, dtype=torch.bfloat16) * 0.05)(640) * 16.0),
    }

def reference(A_x, A_wqkv, A_wo, B_x, B_w_r, B_w_gate, B_w_up, B_w_down, gate_w):
    def _A_ref(x, wqkv, wo):
        B, S, D = x.shape
        H = 32; Dh = D // H
        W, dil = 8, 2
        qkv = (lambda x, *d: x.permute(*d))((x @ wqkv).reshape(B, S, 3, H, Dh), 2, 0, 3, 1, 4)
        q, k, v = qkv[0], qkv[1], qkv[2]
        scale = Dh ** -0.5
        pos = torch.arange(S)
        off = torch.arange(W) * dil
        idx = pos[:, None] - off[None, :]
        mask = idx >= 0
        idx_c = torch.where(mask, idx, 0).reshape(-1)
        kg = k[:, :, idx_c, :].reshape(B, H, S, W, Dh)
        vg = v[:, :, idx_c, :].reshape(B, H, S, W, Dh)
        logits = torch.einsum("bhsd,bhswd->bhsw", q, kg) * scale
        logits = torch.where(mask[None, None, :, :], logits, -1e9)
        attn = _softmax(logits, axis=-1)
        o = torch.einsum("bhsw,bhswd->bhsd", attn, vg)
        return (lambda x, *d: x.permute(*d))(o, 0, 2, 1, 3).reshape(B, S, D) @ wo

    def _B_ref(x, w_r, w_gate, w_up, w_down):
        B, S, D = x.shape
        C = 2
        r = x @ w_r
        idx = torch.argsort(-r, axis=-1)[:, :C]
        idx_e = (lambda x, n, axis: torch.repeat_interleave(x, n, dim=axis))(idx.reshape(B, C, 1), D, axis=2)
        x_sel = (lambda x, i, axis: torch.take_along_dim(x, i, dim=axis))(x, idx_e, axis=1)
        g = _silu(x_sel @ w_gate)
        u = x_sel @ w_up
        y = (g * u) @ w_down
        r_sel = _sigmoid((lambda x, i, axis: torch.take_along_dim(x, i, dim=axis))(r, idx, axis=1))
        y = y * r_sel.reshape(B, C, 1)
        b_off = (torch.arange(B) * S).reshape(B, 1)
        flat_idx = (idx + b_off).reshape(B * C)
        zero = (x * 0.0).reshape(B * S, D)
        upd = _scatter_add(zero, flat_idx, y.reshape(B * C, D), axis=0)
        return x + upd.reshape(B, S, D)

    x = A_x
    g = _sigmoid((x * gate_w).sum(-1, keepdims=True))
    a = _A_ref(x, A_wqkv, A_wo)
    b = _B_ref(x, B_w_r, B_w_gate, B_w_up, B_w_down)
    return g * a + (1 - g) * b
```

```cpp
#include <cuda_runtime.h>
#include <cuda_bf16.h>
#include <cuda.h>
#include <stdint.h>

namespace {

constexpr int NCTA = 128;
constexpr int NFFN = 108;
constexpr uint32_t SENT = 0xFFFFFFFFu;

constexpr uint32_t SB = 1024;
constexpr uint32_t SM_W = SB;
constexpr uint32_t SM_X = SB + 122880;
constexpr uint32_t SM_F = SB + 188416;
constexpr uint32_t SM_G = SB + 212992;
constexpr uint32_t SM_BAR = SB + 223232;
constexpr uint32_t SM_PROF = SB + 223744;
constexpr uint32_t SM_KEY = SB + 224000;
constexpr uint32_t SM_RED = SB + 224128;
constexpr uint32_t SM_XS = SB + 226688;
constexpr uint32_t SM_SENT = SB + 227328;
constexpr uint32_t SM_U = SM_RED + 1920;
constexpr uint32_t SM_GATE = SM_RED;
constexpr uint32_t SM_TOTAL = 232448;
constexpr uint32_t SM_HALO1 = SM_X + 32768;
constexpr uint32_t SM_HALO = SM_HALO1 + 10240;
constexpr uint32_t SM_UP = SM_W + 61440;
constexpr uint32_t SM_OUT = SM_W + 61440;

constexpr uint32_t B_XL0 = SM_BAR, B_FULL = SM_BAR + 8, B_GT = SM_BAR + 72, B_RG = SM_BAR + 80, B_RG2 = SM_BAR + 88,
                   B_XS = SM_BAR + 96, B_EMPTY = SM_BAR + 128, B_DONE = SM_BAR + 192, B_XE = SM_BAR + 200,
                   B_GUD = SM_BAR + 224, B_OE = B_GUD + 8, B_OT = B_GUD + 40, B_MOD = B_GUD + 72,
                   B_GU = SM_BAR + 104, B_ALL = SM_BAR + 112, B_UP = SM_BAR + 120, B_DN = B_GUD + 80, B_RS = B_GUD + 88, B_INIT = B_GUD + 96,
                   B_RE = B_GUD + 104, B_G2 = B_GUD + 112, B_HL = B_GUD + 176;

struct Params {
    CUtensorMap x, x2, w, wr, woa, wob, xg, gate, up, down;
    __nv_bfloat16* op;
    const __nv_bfloat16 *xp, *upp, *wop, *gp, *w_r, *gate_w;
};

constexpr int SC_O = 0;
constexpr int SC_HALO = 1280;
constexpr int SC_GU = 1440;
constexpr int SC_Y = 1504;
constexpr int SC_SIZE = 1600;
__device__ __align__(128) uint4 g_sc[NCTA * SC_SIZE];
__device__ __align__(128) uint4 g_cand[NCTA];
__device__ __align__(16) uint32_t g_gate[2048];
__device__ __align__(128) unsigned g_cnt[64];
#define TS(i) do { } while (0)
#define TS2(i) do { } while (0)
#define TSX(i) do { } while (0)

__device__ __forceinline__ uint32_t smem_u32(const void* p) { return (uint32_t)__cvta_generic_to_shared(p); }
__device__ __forceinline__ void fault() { asm volatile("st.shared.u32 [%0], %0;" ::"r"(0x100001) : "memory"); }
__device__ __forceinline__ void mbar_init(uint32_t bar, uint32_t cnt) {
    asm volatile("mbarrier.init.shared::cta.b64 [%0], %1;" ::"r"(bar), "r"(cnt) : "memory");
}
__device__ __forceinline__ void mbar_expect_tx(uint32_t bar, uint32_t bytes) {
    asm volatile("mbarrier.arrive.expect_tx.shared::cta.b64 _, [%0], %1;" ::"r"(bar), "r"(bytes) : "memory");
}
__device__ __forceinline__ void mbar_arrive(uint32_t bar) {
    asm volatile("mbarrier.arrive.shared::cta.b64 _, [%0];" ::"r"(bar) : "memory");
}
__device__ __forceinline__ bool mbar_try(uint32_t bar, uint32_t parity) {
    uint32_t ok;
    asm volatile("{\n.reg .pred p;\nmbarrier.try_wait.parity.shared::cta.b64 p, [%1], %2;\nselp.u32 %0, 1, 0, p;\n}"
                 : "=r"(ok) : "r"(bar), "r"(parity) : "memory");
    return ok;
}
__device__ __forceinline__ void mbar_wait(uint32_t bar, uint32_t parity) {
    asm volatile("{\n.reg .pred p;\nAGAIN:\nmbarrier.try_wait.parity.shared::cta.b64 p, [%0], %1;\n@!p bra AGAIN;\n}"
                 ::"r"(bar), "r"(parity) : "memory");
}
__device__ __forceinline__ void tma_2d(uint32_t dst, const CUtensorMap* m, uint32_t bar, int c0, int c1) {
    asm volatile("cp.async.bulk.tensor.2d.shared::cluster.global.mbarrier::complete_tx::bytes [%0], [%1, {%3, %4}], [%2];"
                 ::"r"(dst), "l"(m), "r"(bar), "r"(c0), "r"(c1) : "memory");
}
__device__ __forceinline__ void bulk_load(uint32_t dst, const void* src, uint32_t bytes, uint32_t bar) {
    asm volatile("cp.async.bulk.shared::cluster.global.mbarrier::complete_tx::bytes [%0], [%1], %2, [%3];"
                 ::"r"(dst), "l"(src), "r"(bytes), "r"(bar) : "memory");
}
__device__ __forceinline__ void bulk_store(void* dst, uint32_t src, uint32_t bytes) {
    asm volatile("cp.async.bulk.global.shared::cta.bulk_group [%0], [%1], %2;" ::"l"(dst), "r"(src), "r"(bytes) : "memory");
}
__device__ __forceinline__ void tma_3d(uint32_t dst, const CUtensorMap* m, uint32_t bar, int c0, int c1, int c2) {
    asm volatile("cp.async.bulk.tensor.3d.shared::cluster.global.mbarrier::complete_tx::bytes [%0], [%1, {%3, %4, %5}], [%2];"
                 ::"r"(dst), "l"(m), "r"(bar), "r"(c0), "r"(c1), "r"(c2) : "memory");
}
__device__ __forceinline__ void fence_async_smem() { asm volatile("fence.proxy.async.shared::cta;" ::: "memory"); }
__device__ __forceinline__ void wg_fence() { asm volatile("wgmma.fence.sync.aligned;" ::: "memory"); }
__device__ __forceinline__ void wg_commit() { asm volatile("wgmma.commit_group.sync.aligned;" ::: "memory"); }
template <int N> __device__ __forceinline__ void wg_wait() { asm volatile("wgmma.wait_group.sync.aligned %0;" ::"n"(N) : "memory"); }
__device__ __forceinline__ void bar_sync(int id, int n) { asm volatile("bar.cta.sync %0, %1;" ::"r"(id), "r"(n) : "memory"); }
__device__ __forceinline__ void bar_arrive(int id, int n) { asm volatile("bar.cta.arrive %0, %1;" ::"r"(id), "r"(n) : "memory"); }

__device__ constexpr uint32_t desc_lo(uint32_t addr, uint32_t lbo) { return (addr >> 4) | ((lbo >> 4) << 16); }
__device__ __forceinline__ bool elect_one() {
    uint32_t p;
    asm volatile("{\n.reg .pred p;\nelect.sync _|p, 0xffffffff;\nselp.u32 %0, 1, 0, p;\n}" : "=r"(p));
    return p;
}
__device__ __forceinline__ uint32_t ld_relaxed4(const void* p) {
    uint32_t v;
    asm volatile("ld.relaxed.gpu.global.u32 %0, [%1];" : "=r"(v) : "l"(p) : "memory");
    return v;
}
__device__ __forceinline__ void st_relaxed4(void* p, uint32_t v) {
    asm volatile("st.relaxed.gpu.global.u32 [%0], %1;" ::"l"(p), "r"(v) : "memory");
}
__device__ __forceinline__ void red_inc(unsigned* p, unsigned after) {
    asm volatile("red.relaxed.gpu.global.add.u32 [%0], 1;" ::"l"(p), "r"(after) : "memory");
}
__device__ __forceinline__ uint32_t lds4(uint32_t a) {
    uint32_t v;
    asm volatile("ld.shared.u32 %0, [%1];" : "=r"(v) : "r"(a) : "memory");
    return v;
}
__device__ __forceinline__ float2 lds8f(uint32_t a) {
    float2 v;
    asm volatile("ld.shared.v2.f32 {%0, %1}, [%2];" : "=f"(v.x), "=f"(v.y) : "r"(a) : "memory");
    return v;
}
__device__ __forceinline__ void sts4(uint32_t a, uint32_t v) { asm volatile("st.shared.u32 [%0], %1;" ::"r"(a), "r"(v) : "memory"); }
__device__ __forceinline__ uint32_t hmul2(uint32_t a, uint32_t b) {
    uint32_t d;
    asm("mul.rn.bf16x2 %0, %1, %2;" : "=r"(d) : "r"(a), "r"(b));
    return d;
}
__device__ __forceinline__ uint32_t hadd2(uint32_t a, uint32_t b) {
    uint32_t d;
    asm("add.rn.bf16x2 %0, %1, %2;" : "=r"(d) : "r"(a), "r"(b));
    return d;
}
__device__ __forceinline__ uint32_t hfma2(uint32_t a, uint32_t b, uint32_t c) {
    uint32_t d;
    asm("fma.rn.bf16x2 %0, %1, %2, %3;" : "=r"(d) : "r"(a), "r"(b), "r"(c));
    return d;
}
__device__ __forceinline__ uint4 ld_relaxed16(const void* p) {
    uint4 v;
    asm volatile("{\n.reg .b128 t;\n.reg .b64 lo, hi;\nld.relaxed.gpu.global.b128 t, [%4];\nmov.b128 {lo, hi}, t;\n"
                 "mov.b64 {%0, %1}, lo;\nmov.b64 {%2, %3}, hi;\n}" : "=r"(v.x), "=r"(v.y), "=r"(v.z), "=r"(v.w) : "l"(p) : "memory");
    return v;
}
__device__ __forceinline__ void st_relaxed16(void* p, uint32_t a, uint32_t b, uint32_t c, uint32_t d) {
    uint64_t lo = (uint64_t)a | ((uint64_t)b << 32), hi = (uint64_t)c | ((uint64_t)d << 32);
    asm volatile("{\n.reg .b128 t;\nmov.b128 t, {%1, %2};\nst.relaxed.gpu.global.b128 [%0], t;\n}" ::"l"(p), "l"(lo), "l"(hi) : "memory");
}
__device__ __forceinline__ uint4 ld_nc16(const void* p) {
    uint4 v;
    asm volatile("ld.global.nc.L1::no_allocate.v4.u32 {%0, %1, %2, %3}, [%4];" : "=r"(v.x), "=r"(v.y), "=r"(v.z), "=r"(v.w) : "l"(p));
    return v;
}
__device__ __forceinline__ uint4 lds16(uint32_t a) {
    uint4 v;
    asm volatile("ld.shared.v4.u32 {%0, %1, %2, %3}, [%4];" : "=r"(v.x), "=r"(v.y), "=r"(v.z), "=r"(v.w) : "r"(a) : "memory");
    return v;
}
__device__ __forceinline__ void sts16(uint32_t a, uint32_t x, uint32_t y, uint32_t z, uint32_t w) {
    asm volatile("st.shared.v4.u32 [%0], {%1, %2, %3, %4};" ::"r"(a), "r"(x), "r"(y), "r"(z), "r"(w) : "memory");
}
__device__ __forceinline__ uint32_t pack2(float lo, float hi) {
    uint32_t r;
    asm("cvt.rn.bf16x2.f32 %0, %1, %2;" : "=r"(r) : "f"(hi), "f"(lo));
    return r;
}
__device__ __forceinline__ uint32_t pack2v(float lo, float hi) {
    uint32_t r;
    asm volatile("cvt.rn.bf16x2.f32 %0, %1, %2;" : "=r"(r) : "f"(hi), "f"(lo));
    return r;
}
__device__ __forceinline__ float bf_lo(uint32_t u) { return __uint_as_float(u << 16); }
__device__ __forceinline__ float bf_hi(uint32_t u) { return __uint_as_float(u & 0xFFFF0000u); }
__device__ __forceinline__ float bf_round(float f) { return __bfloat162float(__float2bfloat16_rn(f)); }
__device__ __forceinline__ uint32_t movm(uint32_t a) {
    uint32_t d;
    asm volatile("movmatrix.sync.aligned.m8n8.trans.b16 %0, %1;" : "=r"(d) : "r"(a));
    return d;
}
__device__ __forceinline__ void mma16(float (&c)[4], uint32_t a0, uint32_t a1, uint32_t a2, uint32_t a3, uint32_t b0, uint32_t b1) {
    asm volatile("mma.sync.aligned.m16n8k16.row.col.f32.bf16.bf16.f32 {%0,%1,%2,%3}, {%4,%5,%6,%7}, {%8,%9}, {%0,%1,%2,%3};"
                 : "+f"(c[0]), "+f"(c[1]), "+f"(c[2]), "+f"(c[3]) : "r"(a0), "r"(a1), "r"(a2), "r"(a3), "r"(b0), "r"(b1));
}
__device__ __forceinline__ void mma8(float (&c)[4], uint32_t a0, uint32_t a1, uint32_t b0) {
    asm volatile("mma.sync.aligned.m16n8k8.row.col.f32.bf16.bf16.f32 {%0,%1,%2,%3}, {%4,%5}, {%6}, {%0,%1,%2,%3};"
                 : "+f"(c[0]), "+f"(c[1]), "+f"(c[2]), "+f"(c[3]) : "r"(a0), "r"(a1), "r"(b0));
}
__device__ __forceinline__ float ex2(float x) { float y; asm("ex2.approx.ftz.f32 %0, %1;" : "=f"(y) : "f"(x)); return y; }
__device__ __forceinline__ float rcp(float x) { float y; asm("rcp.approx.ftz.f32 %0, %1;" : "=f"(y) : "f"(x)); return y; }
__device__ __forceinline__ float sigmoidf(float z) { return rcp(1.0f + ex2(z * -1.4426950408889634f)); }
__device__ __forceinline__ float u2f(uint32_t u) { return __uint_as_float(u); }
__device__ __forceinline__ uint32_t f2u(float f) { return __float_as_uint(f); }

__device__ __forceinline__ void wgmma_main(float (&d)[96], uint32_t a, uint32_t b, int scale_d) {
    asm volatile("{\n.reg .pred p;\n.reg .b64 da, db;\nsetp.ne.b32 p, %98, 0;\n"
        "mov.b64 da, {%96, 0x40000040};\nmov.b64 db, {%97, 0x40000040};\n"
        "wgmma.mma_async.sync.aligned.m64n192k16.f32.bf16.bf16 "
        "{%0, %1, %2, %3, %4, %5, %6, %7, %8, %9, %10, %11, %12, %13, %14, %15, "
        "%16, %17, %18, %19, %20, %21, %22, %23, %24, %25, %26, %27, %28, %29, %30, %31, "
        "%32, %33, %34, %35, %36, %37, %38, %39, %40, %41, %42, %43, %44, %45, %46, %47, "
        "%48, %49, %50, %51, %52, %53, %54, %55, %56, %57, %58, %59, %60, %61, %62, %63, "
        "%64, %65, %66, %67, %68, %69, %70, %71, %72, %73, %74, %75, %76, %77, %78, %79, "
        "%80, %81, %82, %83, %84, %85, %86, %87, %88, %89, %90, %91, %92, %93, %94, %95}, "
        "da, db, p, 1, 1, 0, 1;\n}\n"
        : "+f"(d[0]), "+f"(d[1]), "+f"(d[2]), "+f"(d[3]), "+f"(d[4]), "+f"(d[5]), "+f"(d[6]), "+f"(d[7]),
          "+f"(d[8]), "+f"(d[9]), "+f"(d[10]), "+f"(d[11]), "+f"(d[12]), "+f"(d[13]), "+f"(d[14]), "+f"(d[15]),
          "+f"(d[16]), "+f"(d[17]), "+f"(d[18]), "+f"(d[19]), "+f"(d[20]), "+f"(d[21]), "+f"(d[22]), "+f"(d[23]),
          "+f"(d[24]), "+f"(d[25]), "+f"(d[26]), "+f"(d[27]), "+f"(d[28]), "+f"(d[29]), "+f"(d[30]), "+f"(d[31]),
          "+f"(d[32]), "+f"(d[33]), "+f"(d[34]), "+f"(d[35]), "+f"(d[36]), "+f"(d[37]), "+f"(d[38]), "+f"(d[39]),
          "+f"(d[40]), "+f"(d[41]), "+f"(d[42]), "+f"(d[43]), "+f"(d[44]), "+f"(d[45]), "+f"(d[46]), "+f"(d[47]),
          "+f"(d[48]), "+f"(d[49]), "+f"(d[50]), "+f"(d[51]), "+f"(d[52]), "+f"(d[53]), "+f"(d[54]), "+f"(d[55]),
          "+f"(d[56]), "+f"(d[57]), "+f"(d[58]), "+f"(d[59]), "+f"(d[60]), "+f"(d[61]), "+f"(d[62]), "+f"(d[63]),
          "+f"(d[64]), "+f"(d[65]), "+f"(d[66]), "+f"(d[67]), "+f"(d[68]), "+f"(d[69]), "+f"(d[70]), "+f"(d[71]),
          "+f"(d[72]), "+f"(d[73]), "+f"(d[74]), "+f"(d[75]), "+f"(d[76]), "+f"(d[77]), "+f"(d[78]), "+f"(d[79]),
          "+f"(d[80]), "+f"(d[81]), "+f"(d[82]), "+f"(d[83]), "+f"(d[84]), "+f"(d[85]), "+f"(d[86]), "+f"(d[87]),
          "+f"(d[88]), "+f"(d[89]), "+f"(d[90]), "+f"(d[91]), "+f"(d[92]), "+f"(d[93]), "+f"(d[94]), "+f"(d[95])
        : "r"(a), "r"(b), "r"(scale_d));
}

__device__ __forceinline__ void wgmma_rem(float (&d)[24], uint32_t a, uint32_t b, int scale_d) {
    asm volatile("{\n.reg .pred p;\n.reg .b64 da, db;\nsetp.ne.b32 p, %26, 0;\n"
        "mov.b64 da, {%24, 0x40000040};\nmov.b64 db, {%25, 0xC0000010};\n"
        "wgmma.mma_async.sync.aligned.m64n48k16.f32.bf16.bf16 "
        "{%0, %1, %2, %3, %4, %5, %6, %7, %8, %9, %10, %11, %12, %13, %14, %15, "
        "%16, %17, %18, %19, %20, %21, %22, %23}, "
        "da, db, p, 1, 1, 0, 1;\n}\n"
        : "+f"(d[0]), "+f"(d[1]), "+f"(d[2]), "+f"(d[3]), "+f"(d[4]), "+f"(d[5]), "+f"(d[6]), "+f"(d[7]),
          "+f"(d[8]), "+f"(d[9]), "+f"(d[10]), "+f"(d[11]), "+f"(d[12]), "+f"(d[13]), "+f"(d[14]), "+f"(d[15]),
          "+f"(d[16]), "+f"(d[17]), "+f"(d[18]), "+f"(d[19]), "+f"(d[20]), "+f"(d[21]), "+f"(d[22]), "+f"(d[23])
        : "r"(a), "r"(b), "r"(scale_d));
}

__device__ __forceinline__ void wgmma_out(float (&d)[80], uint32_t a, uint32_t b, int scale_d) {
    asm volatile("{\n.reg .pred p;\n.reg .b64 da, db;\nsetp.ne.b32 p, %82, 0;\n"
        "mov.b64 da, {%80, 0x50};\nmov.b64 db, {%81, 0x40000040};\n"
        "wgmma.mma_async.sync.aligned.m64n160k16.f32.bf16.bf16 "
        "{%0, %1, %2, %3, %4, %5, %6, %7, %8, %9, %10, %11, %12, %13, %14, %15, "
        "%16, %17, %18, %19, %20, %21, %22, %23, %24, %25, %26, %27, %28, %29, %30, %31, "
        "%32, %33, %34, %35, %36, %37, %38, %39, %40, %41, %42, %43, %44, %45, %46, %47, "
        "%48, %49, %50, %51, %52, %53, %54, %55, %56, %57, %58, %59, %60, %61, %62, %63, "
        "%64, %65, %66, %67, %68, %69, %70, %71, %72, %73, %74, %75, %76, %77, %78, %79}, "
        "da, db, p, 1, 1, 0, 1;\n}\n"
        : "+f"(d[0]), "+f"(d[1]), "+f"(d[2]), "+f"(d[3]), "+f"(d[4]), "+f"(d[5]), "+f"(d[6]), "+f"(d[7]),
          "+f"(d[8]), "+f"(d[9]), "+f"(d[10]), "+f"(d[11]), "+f"(d[12]), "+f"(d[13]), "+f"(d[14]), "+f"(d[15]),
          "+f"(d[16]), "+f"(d[17]), "+f"(d[18]), "+f"(d[19]), "+f"(d[20]), "+f"(d[21]), "+f"(d[22]), "+f"(d[23]),
          "+f"(d[24]), "+f"(d[25]), "+f"(d[26]), "+f"(d[27]), "+f"(d[28]), "+f"(d[29]), "+f"(d[30]), "+f"(d[31]),
          "+f"(d[32]), "+f"(d[33]), "+f"(d[34]), "+f"(d[35]), "+f"(d[36]), "+f"(d[37]), "+f"(d[38]), "+f"(d[39]),
          "+f"(d[40]), "+f"(d[41]), "+f"(d[42]), "+f"(d[43]), "+f"(d[44]), "+f"(d[45]), "+f"(d[46]), "+f"(d[47]),
          "+f"(d[48]), "+f"(d[49]), "+f"(d[50]), "+f"(d[51]), "+f"(d[52]), "+f"(d[53]), "+f"(d[54]), "+f"(d[55]),
          "+f"(d[56]), "+f"(d[57]), "+f"(d[58]), "+f"(d[59]), "+f"(d[60]), "+f"(d[61]), "+f"(d[62]), "+f"(d[63]),
          "+f"(d[64]), "+f"(d[65]), "+f"(d[66]), "+f"(d[67]), "+f"(d[68]), "+f"(d[69]), "+f"(d[70]), "+f"(d[71]),
          "+f"(d[72]), "+f"(d[73]), "+f"(d[74]), "+f"(d[75]), "+f"(d[76]), "+f"(d[77]), "+f"(d[78]), "+f"(d[79])
        : "r"(a), "r"(b), "r"(scale_d));
}

__device__ __forceinline__ void wgmma_own(float (&d)[80], uint32_t a0, uint32_t a1, uint32_t a2, uint32_t a3, uint32_t b, int scale_d) {
    asm volatile("{\n.reg .pred p;\n.reg .b64 db;\nsetp.ne.b32 p, %85, 0;\nmov.b64 db, {%84, 0x40000040};\n"
        "wgmma.mma_async.sync.aligned.m64n160k16.f32.bf16.bf16 "
        "{%0, %1, %2, %3, %4, %5, %6, %7, %8, %9, %10, %11, %12, %13, %14, %15, "
        "%16, %17, %18, %19, %20, %21, %22, %23, %24, %25, %26, %27, %28, %29, %30, %31, "
        "%32, %33, %34, %35, %36, %37, %38, %39, %40, %41, %42, %43, %44, %45, %46, %47, "
        "%48, %49, %50, %51, %52, %53, %54, %55, %56, %57, %58, %59, %60, %61, %62, %63, "
        "%64, %65, %66, %67, %68, %69, %70, %71, %72, %73, %74, %75, %76, %77, %78, %79}, "
        "{%80, %81, %82, %83}, db, p, 1, 1, 1;\n}\n"
        : "+f"(d[0]), "+f"(d[1]), "+f"(d[2]), "+f"(d[3]), "+f"(d[4]), "+f"(d[5]), "+f"(d[6]), "+f"(d[7]),
          "+f"(d[8]), "+f"(d[9]), "+f"(d[10]), "+f"(d[11]), "+f"(d[12]), "+f"(d[13]), "+f"(d[14]), "+f"(d[15]),
          "+f"(d[16]), "+f"(d[17]), "+f"(d[18]), "+f"(d[19]), "+f"(d[20]), "+f"(d[21]), "+f"(d[22]), "+f"(d[23]),
          "+f"(d[24]), "+f"(d[25]), "+f"(d[26]), "+f"(d[27]), "+f"(d[28]), "+f"(d[29]), "+f"(d[30]), "+f"(d[31]),
          "+f"(d[32]), "+f"(d[33]), "+f"(d[34]), "+f"(d[35]), "+f"(d[36]), "+f"(d[37]), "+f"(d[38]), "+f"(d[39]),
          "+f"(d[40]), "+f"(d[41]), "+f"(d[42]), "+f"(d[43]), "+f"(d[44]), "+f"(d[45]), "+f"(d[46]), "+f"(d[47]),
          "+f"(d[48]), "+f"(d[49]), "+f"(d[50]), "+f"(d[51]), "+f"(d[52]), "+f"(d[53]), "+f"(d[54]), "+f"(d[55]),
          "+f"(d[56]), "+f"(d[57]), "+f"(d[58]), "+f"(d[59]), "+f"(d[60]), "+f"(d[61]), "+f"(d[62]), "+f"(d[63]),
          "+f"(d[64]), "+f"(d[65]), "+f"(d[66]), "+f"(d[67]), "+f"(d[68]), "+f"(d[69]), "+f"(d[70]), "+f"(d[71]),
          "+f"(d[72]), "+f"(d[73]), "+f"(d[74]), "+f"(d[75]), "+f"(d[76]), "+f"(d[77]), "+f"(d[78]), "+f"(d[79])
        : "r"(a0), "r"(a1), "r"(a2), "r"(a3), "r"(b), "r"(scale_d));
}

#define TSA(i) do { } while (0)
#define BMAP 3
#define MAP_TILE(b) (((b) & 1) | (((b) >> 1) & 2) | (((b) >> 5) << 2))
#define MAP_HG(b) (((((b) >> 2) & 6) ^ (((b) & 32) ? 6 : 0)) | ((((b) >> 1) ^ ((b) >> 2) ^ ((b) >> 3) ^ ((b) >> 5) ^ BMAP) & 1))
#define SKEW 4
#define PACE 500
#define PACE_W0 (-600)
#define PACE_A 250
#define PACE_B 450
#define RG_T0 1700
#define RG_DT 200
#define RG_ORDER 0x21430
#define GU_N 8
#define GU_T0 3600
#define GU_DT 500
#define RS_T0 10000
#define RS_DT 200
#define EXCH_FIRST 1
#define HALO_D 300
#define PF_UP 7000
#define O_D 0
#define O_DT 300
#define PF_DN 7600
#define PF_DT 450
#define GX_NS 200
#define NRS 2
#define C5_D 600
#define C6_D 100
#define X_EARLY 0
#define X_NODL 0
#define X_PF 5
#define PF_WO 0
#define GH_N 2
#define GH_DT 300
#define PF_LIN 1
#define DN_K 0
#define NB_OWN 1
#define NB_H 1
#define GU_D 500
#define UP_T 0
#define DSPL 0
#define DN0(q) (DSPL ? (q) * 2 + ((q) > 0) : (q) * 3 - ((q) == 3))
#define PF_LIGHT 0
#define FMAP 8
#define UP_DT 0
#define UP_E 1
#define PF_TM 0
#define RS_POS 0
#define X_GUN 10
#define X_NOLD 0
#define X_NODN 0
#define X_NOOWN 0
#define GU_AT 1
#define GX_D 400
#define Y_AT 0
#define WO_HL 9
#define W2_D 0
#define W4_D 0
#define W3_D 0
#define WO_D ((uint64_t)(W2_D / 16) << 16 | (uint64_t)(W4_D / 16) << 24 | (uint64_t)(W3_D / 16) << 32 | (uint64_t)(C5_D / 16) << 40 | (uint64_t)(C6_D / 16) << 48 | (uint64_t)(C6_D / 16) << 56)
#define CAND_T 8300

__device__ __forceinline__ uint32_t keep(uint32_t v) { return __shfl_sync(0xffffffffu, v, threadIdx.x); }
__device__ __forceinline__ uint32_t ukeep(uint32_t v) { return __shfl_sync(0xffffffffu, v, 0); }
__device__ __forceinline__ void ldsm2(uint32_t* d, uint32_t a) {
    asm volatile("ldmatrix.sync.aligned.m8n8.x4.shared.b16 {%0,%1,%2,%3}, [%8];\nldmatrix.sync.aligned.m8n8.x4.shared.b16 {%4,%5,%6,%7}, [%9];"
                 : "=r"(d[0]), "=r"(d[1]), "=r"(d[2]), "=r"(d[3]), "=r"(d[4]), "=r"(d[5]), "=r"(d[6]), "=r"(d[7])
                 : "r"(a), "r"(a ^ 32) : "memory");
}
template <bool SWP, int SEG, int E>
__device__ __forceinline__ void pack_blocks(uint32_t (&d)[10], const float (&am)[96], const float (&ar)[24]) {
#pragma unroll
    for (int t = 0; t < 10; t++) {
        const float* p = (SWP ? t < 2 : t >= 8) ? ar + (SEG * 2 + (t & 1)) * 4 + E : am + (SEG * 8 + t - (SWP ? 2 : 0)) * 4 + E;
        d[t] = pack2v(p[0], p[1]);
    }
}
#define G2MAP 1
#define HALF(hg) ((hg) >> 2)
#define CB(hg) ((hg) & 3)
__device__ __forceinline__ int src_of(int i, int hg) { return i == 0 ? hg : (i - (i <= (hg | 4))) ^ (~hg & 4); }

__device__ constexpr uint32_t o_buf(int i) { return ((0x99ADD1A3u >> ((i - NRS) & 3) * 8) & 255) << 10; }
__device__ constexpr uint32_t wo_buf(int i) { return SM_W + (((X_EARLY ? 0x03241032u : 0x10342103u) >> i * 4) & 7) * 30720; }

template <int N>
__device__ __forceinline__ void poll(uint4 (&a)[N], const uint4* p, int stride) {
    bool bad;
    do {
        bad = false;
#pragma unroll
        for (int s = 0; s < N; s++) a[s] = ld_relaxed16(p + s * stride);
#pragma unroll
        for (int s = 0; s < N; s++) bad |= a[s].w == SENT;
    } while (__any_sync(0xffffffffu, bad));
}
__device__ __forceinline__ void pace(unsigned t0, int t) {
    asm volatile("{\n.reg .pred p;\n.reg .s32 d;\nAGAIN:\nmov.u32 d, %%clock;\nsub.s32 d, d, %0;\nsetp.lt.s32 p, d, 0;\n"
                 "@p nanosleep.u32 20;\n@p bra AGAIN;\n}" ::"r"(t0 + t) : "memory");
}
__device__ __forceinline__ void l2_prefetch(const void* p) { asm volatile("prefetch.global.L2 [%0];" ::"l"(p) : "memory"); }

template <int ROW, int SBO = 1024>
__device__ __forceinline__ void wgmma_vec(float (&d)[8], uint32_t a, uint32_t b, int scale_d) {
    asm volatile("{\n.reg .pred p;\n.reg .b64 da, db;\nsetp.ne.b32 p, %10, 0;\nmov.b64 da, {%8, %12};\nmov.b64 db, {%9, %11};\n"
                 "wgmma.mma_async.sync.aligned.m64n16k16.f32.bf16.bf16 {%0, %1, %2, %3, %4, %5, %6, %7}, da, db, p, 1, 1, 1, 0;\n}"
                 : "+f"(d[0]), "+f"(d[1]), "+f"(d[2]), "+f"(d[3]), "+f"(d[4]), "+f"(d[5]), "+f"(d[6]), "+f"(d[7])
                 : "r"(a), "r"(b), "r"(scale_d), "n"(ROW / 16), "n"(0x40000000 + SBO / 16));
}

__global__ void __launch_bounds__(512, 1) fused_kernel(const __grid_constant__ Params P) {
    extern __shared__ __align__(1024) uint8_t smem_raw[];
    const unsigned t_start = clock();
    const int tid = threadIdx.x, lane = tid & 31;
    const int warp = __shfl_sync(0xffffffffu, tid >> 5, 0);
    const int tile = MAP_TILE(blockIdx.x), hg = MAP_HG(blockIdx.x);
    const int cid = tile * 8 + hg;
    const int par = tile & 1, p0 = (tile >> 1) * 128;
    uint4* const sc = g_sc + cid * SC_SIZE;
    const int fid = FMAP ? ((blockIdx.x - FMAP) & 127) ^ ((blockIdx.x >> 1 ^ BMAP * 2) & 2) : cid;
    const bool swp = (hg & 3) == 3;
    const int wcm = hg * 80 + (swp ? 16 : 0), wcr = hg * 80 + (swp ? 0 : 64);
    if (warp < 7 && elect_one()) {
#pragma unroll
        for (int i = 0; i < 4; i++) mbar_init(SM_BAR + warp * 32 + i * 8, warp < 4 ? 1 : warp < 6 ? 2 : 4);
        asm volatile("fence.mbarrier_init.release.cluster;" ::: "memory");
        if (warp == 0) {
            mbar_expect_tx(B_FULL, 15360 + 8192);
            tma_3d(SM_X + 8192, &P.x, B_FULL, 0, par, p0 + 64);
            tma_3d(SM_W, &P.w, B_FULL, wcm, 0, 0);
            tma_3d(SM_W + 12288, &P.wr, B_FULL, wcr, 0, 0);
            TS(40);
            mbar_expect_tx(B_XL0, 8192);
            tma_3d(SM_X, &P.x, B_XL0, 0, par, p0);
        }
    }
    __syncthreads();

    if (warp >= 12) {
        asm volatile("setmaxnreg.dec.sync.aligned.u32 32;");
        if (warp == 12) {
            if (elect_one()) {
#pragma unroll 1
                for (int s = 1; s < 20; s++) {
                    const uint32_t fb = B_FULL + (s & 7) * 8, dst = SM_W + (s & 7) * 15360;
                    mbar_wait(fb + (B_EMPTY - B_FULL), ~(s >> 3) & 1);
                    pace(t_start, max(PACE_A + s * PACE_B, PACE_W0 + s * PACE));
                    mbar_expect_tx(fb, (s & 1) ? 15360 : 15360 + 16384);
                    tma_3d(dst, &P.w, fb, wcm, s * 32, 0);
                    tma_3d(dst + 12288, &P.wr, fb, wcr, s * 32, 0);
                    TS2(20 + s);
                    if (s == 1) TS(41);
                }
                mbar_wait(B_RG2, 0);
                if (fid < NFFN) {
                    mbar_expect_tx(B_UP, 30720);
                    mbar_wait(B_EMPTY + 5 * 8, 1);
                    TS(42);
                    tma_2d(SM_UP + 10240, &P.up, B_UP, (fid >> 2) * 64, (fid & 3) * 160);
#pragma unroll
                    for (int i = 0; i < GH_N; i++)
                        tma_2d(SM_UP + i * (10240 / GH_N), &P.gate, B_UP, (fid >> 2) * 64, (fid & 3) * 160 + 80 + i * (80 / GH_N));
                    TS(46);
                }
                const int cb = CB(hg), ca = (cb * 5 + 1) >> 1, cr = cb * 160 + ((cb & 1) ? 0 : 128);
                unsigned t1 = 0;
#pragma unroll 1
                for (int j = 0; j < 8; j++) {
                    const int i = j ^ (j == 3 || j == 4 ? 7 : 0);
                    if (j == WO_HL) mbar_wait(B_HL, 0);
                    if (j != 3) mbar_wait(j < 3 ? B_EMPTY + ((2 * j + 7) & 7) * 8 : B_GUD + (j - 4) * 8, j == 0);
                    if (j != 3 && j != 4) t1 = clock();
                    pace(t1, (WO_D >> j * 8 & 255) * 16);
                    const uint32_t dst = wo_buf(i), gb = B_G2 + i * 8;
                    mbar_expect_tx(gb, 25600);
                    tma_3d(dst, &P.woa, gb, 0, src_of(i, hg) * 80, ca);
                    tma_2d(dst + 20480, &P.wob, gb, cr, src_of(i, hg) * 80);
                }
            }
        } else if (warp == 14) {
            if (elect_one()) {
#pragma unroll 1
                for (int kb = 1; kb < 10; kb++) {
                    const uint32_t fb = B_FULL + (kb & 3) * 16, dst = SM_X + (kb & 3) * 16384;
                    mbar_wait(fb + (B_EMPTY - B_FULL + 8), ~(kb >> 2) & 1);
                    if (kb >= 4) mbar_wait(B_XE + (kb - 4 >> 1) * 8, 0);
                    pace(t_start, max(PACE_A - PACE_B / 2 + 2 * kb * PACE_B, PACE_W0 - 50 + (2 * kb + 1) * PACE));
                    tma_3d(dst, &P.x2, fb, kb * 64, par, p0);
                }
            }
            __syncwarp();
            mbar_wait(B_ALL, 0);
            bar_sync(12, 64);
            pace(clock(), HALO_D);
            uint4 hv[5];
            poll<5>(hv, sc + (SC_HALO - (tile < 2 ? 0 : 16 * SC_SIZE) + lane), 32);
#pragma unroll
            for (int s = 0; s < 5; s++) sts16(SM_HALO + s * 512 + lane * 16, hv[s].x, hv[s].y, hv[s].z, hv[s].w);
            bar_arrive(8, 64);
            if (lane < 2) mbar_arrive(B_HL);
            TS(25);
        } else if (warp == 15) {
#pragma unroll 1
            for (int i = 0; i < (fid < NFFN ? X_PF : 0); i++) {
                pace(t_start, PF_UP + i * PF_DT);
                const int ln = i < 5 ? (i * 108 + fid) * 32 + lane : (fid >> 2) * 80 + (fid & 3) * 4320 + 2160 + (i - 5) * 27 + min(lane, 26);
                l2_prefetch((i < 5 ? P.upp : P.gp) + ln * 64);
            }
            int it = smem_u32(smem_raw) == SB ? 0 : 1 << 20;
            while (!mbar_try(B_DONE, 0) || !mbar_try(B_MOD, 0))
                if (++it > (1 << 20)) fault();
        } else {
#pragma unroll 1
            for (int i = 0; i < 10; i++) sts16(SM_SENT + i * 512 + lane * 16, SENT, SENT, SENT, SENT);
            fence_async_smem();
            __syncwarp();
            if (elect_one()) {
                mbar_expect_tx(B_RG, 2560);
                asm volatile("mbarrier.expect_tx.relaxed.cta.shared::cta.b64 [%0], 10240;" ::"r"(B_RG2) : "memory");
                bulk_load(SM_RED, P.w_r, 1280, B_RG);
                bulk_load(SM_RED + 1280, P.gate_w, 1280, B_RG);
#pragma unroll
                for (int i = 0; i < 23; i++) mbar_init(B_GUD + i * 8, i == 0 ? 4 : i < 15 + NRS ? 1 : 2);
#pragma unroll 1
                for (int i = 0; i < 5; i++) {
                    pace(t_start, RG_T0 + i * RG_DT);
                    tma_3d(SM_G + i * 2048, &P.xg, B_RG2, 320 + i * 64, par, p0 + hg * 16);
                    if (RS_POS == 2) bulk_store(sc + i * 320, SM_SENT, 5120);
                }
                bulk_store(sc + SC_HALO, SM_SENT, 5120);
                asm volatile("cp.async.bulk.commit_group;\ncp.async.bulk.wait_group 0;" ::: "memory");
                mbar_arrive(B_RG2);
                TS(43);
                const unsigned goal = (ld_relaxed4(g_cnt + 32) | (NCTA - 1)) + 1;
                const int nd = fid < NFFN ? 6 - (DSPL ? (fid + 1) & 2 : fid & 2) : 0;
                mbar_expect_tx(B_DN, nd * 4096);
#pragma unroll 1
                for (int i = 0; i < nd; i++) {
                    pace(t_start, GU_T0 + i * GU_DT);
                    tma_3d(SM_F + i * 4096, &P.down, B_DN, 0, (fid >> 2) * 64 + (i & 1) * 32, DN0(fid & 3) + (i >> 1));
                }
#pragma unroll 1
                for (int i = 0; i < 4; i++) {
                    pace(t_start, RS_T0 + i * RS_DT);
                    bulk_store(sc + i * 320, SM_SENT, 5120);
                }
                asm volatile("cp.async.bulk.commit_group;\ncp.async.bulk.wait_group 0;" ::: "memory");
                red_inc(g_cnt + 32, goal);
                mbar_arrive(B_RS);
                TS(44);
                while (ld_relaxed4(g_cnt + 32) - goal > 0x80000000u) {}
                mbar_arrive(B_INIT);
                TS(45);
            }
        }
    } else if (warp >= 8) {
        asm volatile("setmaxnreg.dec.sync.aligned.u32 96;");
        const int t = tid - 256;
        const unsigned epoch = ld_relaxed4(g_cnt) / NCTA + 1;
        float gv = 0.f;
        int grow = hg * 16 + (t >> 3);
        mbar_wait(B_RG, 0);
        TS(warp == 8 ? 48 : 63);
        {
            float r0 = 0.f, r1 = 0.f, g0 = 0.f, g1 = 0.f;
            const uint32_t sw = (t >> 4) * 128 + (((t ^ (t >> 4)) & 7) << 4), hi = (t >> 3) & 1;
            mbar_wait(B_XL0, 0);
#pragma unroll 1
            for (int i = 0; i < 5; i++) {
                const int p = (RG_ORDER >> (i * 4)) & 7, kb = 2 * p + hi;
                mbar_wait(p < 3 ? B_FULL + (p & 1) * 32 : B_RG2, p == 2);
                if (p < 2) mbar_wait(B_FULL + p * 32 + 16, 0);
                const uint32_t xa = sw + (kb < 5 ? SM_X + (kb & 3) * 16384 + hg * 2048 : SM_G - 5 * 2048 + kb * 2048);
                const uint4 a = lds16(xa), b = lds16(xa + 1024);
                const uint4 w = lds16(SM_RED + p * 256 + (t & 15) * 16), v = lds16(SM_RED + 1280 + p * 256 + (t & 15) * 16);
                if (__ballot_sync(0xffffffffu, lane == 0 || a.w == b.w) && lane == 0 && p < 3) mbar_arrive(B_XE + p * 8);
                const uint32_t as[4] = {a.x, a.y, a.z, a.w}, bs[4] = {b.x, b.y, b.z, b.w};
                const uint32_t ws[4] = {w.x, w.y, w.z, w.w}, vs[4] = {v.x, v.y, v.z, v.w};
#pragma unroll
                for (int e = 0; e < 4; e++) {
                    r0 = fmaf(bf_lo(as[e]), bf_lo(ws[e]), r0);
                    r1 = fmaf(bf_lo(bs[e]), bf_lo(ws[e]), r1);
                    g0 = fmaf(bf_lo(as[e]), bf_lo(vs[e]), g0);
                    g1 = fmaf(bf_lo(bs[e]), bf_lo(vs[e]), g1);
                    r0 = fmaf(bf_hi(as[e]), bf_hi(ws[e]), r0);
                    r1 = fmaf(bf_hi(bs[e]), bf_hi(ws[e]), r1);
                    g0 = fmaf(bf_hi(as[e]), bf_hi(vs[e]), g0);
                    g1 = fmaf(bf_hi(bs[e]), bf_hi(vs[e]), g1);
                }
            }
            const bool up = lane & 4;
            r0 = (hi ? r1 : r0) + __shfl_xor_sync(0xffffffffu, hi ? r0 : r1, 8);
            g0 = (hi ? g1 : g0) + __shfl_xor_sync(0xffffffffu, hi ? g0 : g1, 8);
            float r = (up ? g0 : r0) + __shfl_xor_sync(0xffffffffu, up ? r0 : g0, 4);
            r += __shfl_xor_sync(0xffffffffu, r, 2);
            r = bf_round(r + __shfl_xor_sync(0xffffffffu, r, 1));
            const int row = hg * 16 + (t >> 4) + hi * 8;
            const uint32_t u = f2u(r);
            if (!up) sts4(SM_KEY + (t >> 3) * 4, (((int)u < 0 ? ~u : u | 0x80000000u) & 0xFFFF0000u) | (2047 - (p0 + row) * 2 - par));
            gv = r;
            grow = row;
        }
        bar_sync(4, 128);
        if (warp == 10 && fid < NFFN && elect_one()) {
            mbar_expect_tx(B_GU, 10240);
#pragma unroll 1
            for (int i = 0; i < GH_N; i++) {
                if (i) pace(clock(), GH_DT);
                tma_2d(SM_G + i * (10240 / GH_N), &P.gate, B_GU, (fid >> 2) * 64, (fid & 3) * 160 + i * (80 / GH_N));
            }
        }
        if (warp == 8) {
            const uint32_t key = lds4(SM_KEY + (lane & 15) * 4);
            uint32_t k1 = __reduce_max_sync(0xffffffffu, key);
            uint32_t k2 = __reduce_max_sync(0xffffffffu, key == k1 ? 0u : key);
            if (elect_one()) {
                st_relaxed16(g_cand + cid, k1, k2, epoch, epoch);
                red_inc(g_cnt, epoch);
            }
            TS(49);
        }
        if ((lane & 7) == 4) st_relaxed4(g_gate + tile * 128 + grow, f2u(bf_round(sigmoidf(gv))) | (epoch & 0xFFFFu));
        pace(t_start, CAND_T);
        if (warp == 9) {
            uint4 v;
            do {
                asm volatile("ld.relaxed.gpu.global.v4.u32 {%0, %1, %2, %3}, [%4];"
                             : "=r"(v.x), "=r"(v.y), "=r"(v.z), "=r"(v.w) : "l"(g_gate + tile * 128 + lane * 4) : "memory");
            } while (__any_sync(0xffffffffu, ((v.x ^ epoch) | (v.y ^ epoch) | (v.z ^ epoch) | (v.w ^ epoch)) & 0xFFFFu));
            sts16(SM_GATE + lane * 16, v.x, v.y, v.z, v.w);
            __syncwarp();
            if (lane == 0) mbar_arrive(B_GT);
            TS(47);
        }
        if (warp == 8) {
            uint4 cd[4];
            do {
#pragma unroll
                for (int j = 0; j < 4; j++) cd[j] = ld_relaxed16(g_cand + lane + 32 * j);
            } while (!__all_sync(0xffffffffu, cd[0].z == epoch && cd[1].z == epoch && cd[2].z == epoch && cd[3].z == epoch));
            uint32_t l1 = 0, l2 = 0;
#pragma unroll
            for (int j = 0; j < 4; j++) {
                l2 = max(max(l2, cd[j].y), min(l1, cd[j].x));
                l1 = max(l1, cd[j].x);
            }
            const uint32_t k1 = __reduce_max_sync(0xffffffffu, l1);
            const uint32_t k2 = __reduce_max_sync(0xffffffffu, l1 == k1 ? l2 : l1);
            if (elect_one()) {
                bulk_load(SM_XS, P.xp + (~k1 & 2047) * 640 + (fid & 3) * 160, 320, B_XS);
                bulk_load(SM_XS + 320, P.xp + (~k2 & 2047) * 640 + (fid & 3) * 160, 320, B_XS);
                sts16(SM_KEY + 16 * 4, k1, k2, 0, 0);
                mbar_expect_tx(B_XS, 640);
                mbar_arrive(B_ALL);
                TS(56);
            }
        }
        mbar_wait(B_XS, 0);
        TS(warp == 8 ? 50 : 63);
        const int cq = lane & 3, q = fid & 3;
        if (fid < NFFN) {
            uint4* const sc = g_sc + fid * SC_SIZE;
            float ga[8], ua[8];
            mbar_wait(B_GU, 0);
            TS(warp == 8 ? 61 : 63);
            mbar_wait(B_UP, 0);
            TS(warp == 8 ? 58 : 63);
            if (GU_AT == 6) {
                mbar_wait(B_EMPTY + 3 * 8, 0);
                const unsigned c0 = clock();
                while ((unsigned)clock() - c0 < GU_D) {}
            } else if (GU_AT) bar_sync(13, GU_AT == 3 || GU_AT == 5 ? 224 : 256);
            TS(warp == 8 ? 53 : 63);
            wg_fence();
#pragma unroll
            for (int i = 0; i < X_GUN; i++) {
                wgmma_vec<320>(ga, desc_lo(i < 5 ? SM_G : SM_UP - 10240, 16) + i * 128, desc_lo(SM_XS, 16) + i * 2, i);
                wgmma_vec<320>(ua, desc_lo(SM_UP + 10240, 16) + i * 128, desc_lo(SM_XS, 16) + i * 2, i);
            }
            wg_commit();
            wg_wait<0>();
            TS(warp == 8 ? 54 : 63);
            if (cq == 0) {
                st_relaxed16(sc + SC_GU + (t >> 2), f2u(ga[0]), f2u(ga[2]), f2u(ga[4]), f2u(ga[6]));
                st_relaxed16(sc + SC_GU + 32 + (t >> 2), f2u(ua[0]), f2u(ua[2]), f2u(ua[4]), f2u(ua[6]));
            }
            if (lane == 0) mbar_arrive(B_GUD);
            if (!X_NODN) {
            uint4 pq[2];
            pace(clock(), GX_D);
            poll<2>(pq, sc + (cq - q) * SC_SIZE + SC_GU + (t >> 2), 32);
            TS(warp == 8 ? 55 : 63);
            const bool tk = cq & 2, c8 = cq & 1;
            float v[4];
#pragma unroll
            for (int m = 0; m < 2; m++) {
                v[2 * m] = u2f(tk ? pq[m].z : pq[m].x) + __shfl_xor_sync(0xffffffffu, u2f(tk ? pq[m].x : pq[m].z), 2);
                v[2 * m + 1] = u2f(tk ? pq[m].w : pq[m].y) + __shfl_xor_sync(0xffffffffu, u2f(tk ? pq[m].y : pq[m].w), 2);
                v[m] = bf_round((c8 ? v[2 * m + 1] : v[2 * m]) + __shfl_xor_sync(0xffffffffu, c8 ? v[2 * m] : v[2 * m + 1], 1));
            }
            const uint32_t h = pack2(bf_round(v[0] * sigmoidf(v[0])) * v[1], 0.f);
            asm volatile("st.shared.u16 [%0], %1;" ::"r"(SM_XS + (cq >> 1) * 128 + ((t >> 5) * 16 + (cq & 1) * 8 + (lane >> 2)) * 2),
                         "h"((uint16_t)h) : "memory");
            fence_async_smem();
            bar_sync(4, 128);
            TS(warp == 8 ? 57 : 63);
            mbar_wait(B_DN, 0);
            bar_sync(14, 384);
            TS(warp == 8 ? 59 : 63);
            float y[3][8];
#pragma unroll 1
            for (int i = 0; i < 4; i++) {
                wg_fence();
#pragma unroll
                for (int m = 0; m < 3; m++)
                    if (DN_K) wgmma_vec<128, 3072>(y[m], desc_lo(SM_F + m * 1024, 16) + i * 384, desc_lo(SM_XS, 16) + i * 2, i);
                    else wgmma_vec<128>(y[m], desc_lo(SM_F + m * 8192, 16) + i * 128, desc_lo(SM_XS, 16) + i * 2, i);
                wg_commit();
            }
            wg_wait<0>();
            if (cq == 0) {
#pragma unroll
                for (int m = 0; m < 6; m++)
                    asm volatile("st.relaxed.gpu.global.v2.f32 [%0], {%1, %2};"
                                 ::"l"(reinterpret_cast<float2*>(sc + SC_Y) + (m & 1) * 96 + (m >> 1) * 32 + (t >> 2)),
                                   "f"(y[m >> 1][(m & 1) * 4]), "f"(y[m >> 1][(m & 1) * 4 + 2]) : "memory");
            }
            }
        } else if (lane == 0) {
            mbar_arrive(B_GUD);
        }
        TS(warp == 8 ? 51 : 63);
        const uint32_t k1 = lds4(SM_KEY + 16 * 4), k2 = lds4(SM_KEY + 17 * 4);
        const uint32_t mine = (tile >> 1) * 256 + HALF(hg) * 128 + par;
        const bool own1 = (~k1 & 0x781) == mine, own2 = (~k2 & 0x781) == mine;
        if ((own1 || own2) && NFFN && !X_NODN && !X_NOOWN) {
            const int rg = min(t / 40, 2), c40 = t % 40, un = CB(hg) * 40 + c40, src = DSPL ? min(max(un - 16, 0) >> 5, 3) : un < 48 ? 0 : un < 96 ? 1 : un < 128 ? 2 : 3;
            mbar_wait(B_OE + Y_AT * 8, 0);
            TS(warp == 8 ? 60 : 63);
#pragma unroll 1
            for (int j = !own1; j <= own2; j++) {
                const uint4* p = g_sc + (rg * 4 + src) * SC_SIZE + SC_Y + j * 48 + un - DN0(src) * 16;
                float y[4];
                bool bad;
                do {
                    uint4 yp[9];
#pragma unroll
                    for (int i = 0; i < 9; i++) yp[i] = ld_relaxed16(p + i * 12 * SC_SIZE);
                    y[0] = y[1] = y[2] = y[3] = 0.f;
                    bad = false;
#pragma unroll
                    for (int i = 0; i < 9; i++) {
                        y[0] += u2f(yp[i].x); y[1] += u2f(yp[i].y); y[2] += u2f(yp[i].z); y[3] += u2f(yp[i].w);
                        bad |= max(max(yp[i].x, yp[i].y), max(yp[i].z, yp[i].w)) == SENT;
                    }
                } while (__any_sync(0xffffffffu, bad));
                TS(warp == 8 ? 62 : 63);
                sts16(SM_F + j * 2048 + t * 16, f2u(y[0]), f2u(y[1]), f2u(y[2]), f2u(y[3]));
                bar_sync(4, 128);
                if (t < 80) {
                    const uint32_t key = j ? k2 : k1, ya = SM_F + j * 2048 + (t >> 1) * 16 + (t & 1) * 4;
                    const float rs = bf_round(sigmoidf(u2f(((int)key < 0 ? key & 0x7FFFFFFFu : ~key) & 0xFFFF0000u)));
                    const float y0 = u2f(lds4(ya)) + u2f(lds4(ya + 640)) + u2f(lds4(ya + 1280));
                    const float y1 = u2f(lds4(ya + 8)) + u2f(lds4(ya + 648)) + u2f(lds4(ya + 1288));
                    sts4(SM_U + j * 320 + (t >> 3) * 32 + (t & 1) * 16 + (t & 6) * 2, pack2(bf_round(y0) * rs, bf_round(y1) * rs));
                }
            }
            bar_sync(4, 128);
        }
        if (t == 0) mbar_arrive(B_MOD);
        TS(warp == 8 ? 52 : 63);
    } else {
        asm volatile("setmaxnreg.inc.sync.aligned.u32 192;");
        const int wg = warp >> 2;
        const bool leader = (tid & 127) == 0;
        float am[96], ar[24];
        if (wg == 0) mbar_wait(B_XL0, 0);
        bool rel = false;
        uint32_t nb[40];
        const int odd = CB(hg) & 1, kba = ukeep(wg == HALF(hg) || !NB_OWN ? (CB(hg) * 5 + 1) >> 1 : 16), kbr = ukeep(kba + 2 - odd * 3);
        const int kbs = wg ? -1 : (20 - SKEW) / 2;
        const uint32_t xrow = keep(SM_X + (warp * 16 + (lane & 15)) * 128 + (((lane >> 4) ^ (lane & 7)) << 4));
#pragma unroll 1
        for (int kb = 0; kb < 10; kb++) {
            const uint32_t fb = B_FULL + (kb & 3) * 16, wo = (kb & 3) * 1920, ph = (kb >> 2) & 1;
            const uint32_t xo = desc_lo(SM_X, 16) + wg * 512 + (kb & 3) * 1024;
#pragma unroll
            for (int h = 0; h < 2; h++) {
                mbar_wait(fb + h * 8, ph);
                if (kb == 0 && h == 0) TS(warp == 0 ? 0 : warp == 4 ? 16 : 63);
                TS2(warp == 4 ? kb * 2 + h : 63);
                if (h == NB_H) {
                    const uint32_t xa = xrow + (kb & 3) * 16384;
                    if (kb == kba) { ldsm2(nb, xa); ldsm2(nb + 8, xa ^ 64); }
                    if (kb == kba + 1) { ldsm2(nb + 16, xa); ldsm2(nb + 24, xa ^ 64); }
                    if (kb == kbr) ldsm2(nb + 32, xa ^ (odd * 64));
                }
                wg_wait<1>();
                if (rel) mbar_arrive(B_EMPTY + ((kb * 16 - 16) & 48) + h * 8);
                if (h == (SKEW & 1) && kb == kbs) bar_sync(5, 256);
                wg_fence();
                wgmma_main(am, xo + h * 4, desc_lo(SM_W + h * 15360, 4096) + wo, h || kb);
                wgmma_rem(ar, xo + h * 4, desc_lo(SM_W + h * 15360 + 12288, 1024) + wo, h || kb);
                wgmma_main(am, xo + h * 4 + 2, desc_lo(SM_W + h * 15360 + 2048, 4096) + wo, 1);
                wgmma_rem(ar, xo + h * 4 + 2, desc_lo(SM_W + h * 15360 + 12288 + 512, 1024) + wo, 1);
                wg_commit();
            }
            rel = leader;
        }
        if (wg == 1) bar_arrive(5, 256);
        if (GU_AT == 1 && wg == 0) bar_arrive(13, 256);
        mbar_wait(B_XE + 16, 0);
        mbar_wait(B_EMPTY + 7 * 8 - wg * 16, 1);
        wg_wait<0>();
        if (leader) mbar_arrive(B_EMPTY + 3 * 8);
        TS(warp == 0 ? 2 : warp == 4 ? 18 : 63);

        uint32_t kl[10], kh[10], vl[10], vh[10], ql[10], qh[10], kp[10], vp[10];
        if (swp) {
            pack_blocks<true, 1, 2>(kh, am, ar);
            pack_blocks<true, 2, 2>(vh, am, ar);
        } else {
            pack_blocks<false, 1, 2>(kh, am, ar);
            pack_blocks<false, 2, 2>(vh, am, ar);
        }
        const int w4 = warp & 3;
        const uint32_t pbuf = (wg ? SM_HALO1 : SM_HALO) + w4 * 2560 + lane * 16;
        const uint32_t hbuf = warp == 3 ? SM_HALO1 + lane * 16 : pbuf + 2560;
        {
            const uint32_t ex[20] = {kh[0], kh[1], kh[3], kh[4], kh[5], kh[6], kh[8], kh[9], kh[2], kh[7],
                                     vh[0], vh[1], vh[2], vh[3], vh[4], vh[5], vh[6], vh[7], vh[8], vh[9]};
            if (warp == 7) {
                uint4* const hp = sc + SC_HALO + lane;
#pragma unroll
                for (int s = 0; s < 5; s++) st_relaxed16(hp + s * 32, ex[4 * s], ex[4 * s + 1], ex[4 * s + 2], ex[4 * s + 3]);
                bar_arrive(12, 64);
            } else {
#pragma unroll
                for (int s = 0; s < 5; s++) sts16(hbuf + s * 512, ex[4 * s], ex[4 * s + 1], ex[4 * s + 2], ex[4 * s + 3]);
            }
        }
        TSA(warp == 7 ? 22 : warp == 3 ? 23 : 63);
        if (warp == 3) bar_arrive(11, 64);
        if (swp) {
            pack_blocks<true, 2, 0>(vl, am, ar);
            pack_blocks<true, 0, 0>(ql, am, ar);
            pack_blocks<true, 0, 2>(qh, am, ar);
            pack_blocks<true, 1, 0>(kl, am, ar);
        } else {
            pack_blocks<false, 2, 0>(vl, am, ar);
            pack_blocks<false, 0, 0>(ql, am, ar);
            pack_blocks<false, 0, 2>(qh, am, ar);
            pack_blocks<false, 1, 0>(kl, am, ar);
        }
#pragma unroll
        for (int t = 0; t < 10; t++) { vl[t] = movm(vl[t]); vh[t] = movm(vh[t]); }
        if (RS_POS == 0) mbar_wait(B_RS, 0);
        mbar_wait(B_GT, 0);
        const float g0 = bf_hi(lds4(SM_GATE + warp * 64 + (lane & 28))), g1 = bf_hi(lds4(SM_GATE + 32 + warp * 64 + (lane & 28)));

        const int r = lane >> 2, cq = lane & 3;
        const bool no_prev = warp == 0 && tile < 2, low = cq < 2;
        const bool le0 = 2 * cq <= r, le1 = 2 * cq + 1 <= r;
        const uint32_t mle = (le0 ? 0xFFFFu : 0u) | (le1 ? 0xFFFF0000u : 0u);
        const float scl = 0.22360679774997896f * 1.4426950408889634f;
        uint32_t pl[4], ph[4];
        {
            float sl[4][4], sh[4][4], sp[4][4];
            auto exchange = [&]() {
            TSA(warp == 1 ? 26 : 63);
            bar_sync(6 + wg, 128);
            if (w4 == 0) bar_sync(8 + wg * 3, 64);
            {
                const uint4 a = lds16(pbuf), b = lds16(pbuf + 512), c = lds16(pbuf + 1024), d = lds16(pbuf + 1536), e = lds16(pbuf + 2048);
                kp[0] = a.x; kp[1] = a.y; kp[3] = a.z; kp[4] = a.w; kp[5] = b.x; kp[6] = b.y; kp[8] = b.z; kp[9] = b.w;
                kp[2] = c.x; kp[7] = c.y; vp[0] = c.z; vp[1] = c.w; vp[2] = d.x; vp[3] = d.y; vp[4] = d.z; vp[5] = d.w;
                vp[6] = e.x; vp[7] = e.y; vp[8] = e.z; vp[9] = e.w;
            }
            TSA(warp == 0 ? 3 : warp == 4 ? 19 : warp == 5 ? 27 : 63);
            };
            if (EXCH_FIRST) exchange();
#pragma unroll
            for (int h = 0; h < 4; h++) {
                const int ta = (h >> 1) * 5 + (h & 1) * 3, tc = (h >> 1) * 5 + 2;
                const uint32_t ml = low != (h & 1) ? ql[tc] : 0u, mh = low != (h & 1) ? qh[tc] : 0u;
#pragma unroll
                for (int e = 0; e < 4; e++) sl[h][e] = sh[h][e] = sp[h][e] = 0.f;
                mma16(sl[h], ql[ta], qh[ta], ql[ta + 1], qh[ta + 1], kl[ta], kl[ta + 1]);
                mma16(sh[h], ql[ta], qh[ta], ql[ta + 1], qh[ta + 1], kh[ta], kh[ta + 1]);
                mma8(sl[h], ml, mh, kl[tc]);
                mma8(sh[h], ml, mh, kh[tc]);
            }
            if (!EXCH_FIRST) exchange();
#pragma unroll
            for (int h = 0; h < 4; h++) {
                const int ta = (h >> 1) * 5 + (h & 1) * 3, tc = (h >> 1) * 5 + 2;
                mma16(sp[h], ql[ta], qh[ta], ql[ta + 1], qh[ta + 1], kp[ta], kp[ta + 1]);
                mma8(sp[h], low != (h & 1) ? ql[tc] : 0u, low != (h & 1) ? qh[tc] : 0u, kp[tc]);
            }
            if (GU_AT == 2 && wg == 1) bar_arrive(13, 256);
            if (GU_AT == 3 && warp > 4) bar_arrive(13, 224);
            if (GU_AT == 4 && wg == 0) bar_arrive(13, 256);
            if (GU_AT == 5 && wg == 0 && warp) bar_arrive(13, 224);
#pragma unroll
            for (int t = 0; t < 10; t++) vp[t] = movm(vp[t]);
#pragma unroll
            for (int h = 0; h < 4; h++) {
                if (no_prev) sp[h][0] = sp[h][1] = -1e9f / 0.22360679774997896f;
                const float a0 = le0 ? sl[h][0] : sp[h][0], a1 = le1 ? sl[h][1] : sp[h][1];
                const float b0 = le0 ? sh[h][2] : sl[h][2], b1 = le1 ? sh[h][3] : sl[h][3];
                float ma = fmaxf(a0, a1), mb = fmaxf(b0, b1);
                ma = fmaxf(ma, __shfl_xor_sync(0xffffffffu, ma, 1));
                mb = fmaxf(mb, __shfl_xor_sync(0xffffffffu, mb, 1));
                ma = fmaxf(ma, __shfl_xor_sync(0xffffffffu, ma, 2)) * -scl;
                mb = fmaxf(mb, __shfl_xor_sync(0xffffffffu, mb, 2)) * -scl;
                pl[h] = pack2(ex2(fmaf(a0, scl, ma)), ex2(fmaf(a1, scl, ma)));
                ph[h] = pack2(ex2(fmaf(b0, scl, mb)), ex2(fmaf(b1, scl, mb)));
            }
        }
        TSA(warp == 0 ? 4 : warp == 4 ? 20 : warp == 5 ? 28 : 63);
        uint32_t ol[10], oh[10];
        {
            uint32_t* const po = reinterpret_cast<uint32_t*>(sc + SC_O + warp * 160) + lane;
            const uint32_t ONES = 0x3F803F80u;
            float o[12][4];
#pragma unroll
            for (int hp = 0; hp < 2; hp++) {
#pragma unroll
                for (int h = hp * 2; h < hp * 2 + 2; h++) {
                    const int ta = (h >> 1) * 5 + (h & 1) * 3, tc = (h >> 1) * 5 + 2;
                    const bool mine = (lane < 16) != (h & 1);
                    const uint32_t a0 = pl[h] & mle, a1 = ph[h] & ~mle, a3 = ph[h] & mle, ap = pl[h] & ~mle;
#pragma unroll
                    for (int i = 0; i < 3; i++) o[h * 3 + i][0] = o[h * 3 + i][1] = o[h * 3 + i][2] = o[h * 3 + i][3] = 0.f;
                    mma16(o[h * 3 + 2], a0, a1, 0u, a3, mine ? vl[tc] : ONES, mine ? vh[tc] : ONES);
                    mma16(o[h * 3], a0, a1, 0u, a3, vl[ta], vh[ta]);
                    mma16(o[h * 3 + 1], a0, a1, 0u, a3, vl[ta + 1], vh[ta + 1]);
                    mma8(o[h * 3 + 2], ap, 0u, mine ? vp[tc] : ONES);
                    mma8(o[h * 3], ap, 0u, vp[ta]);
                    mma8(o[h * 3 + 1], ap, 0u, vp[ta + 1]);
                }
                if (hp && wg != HALF(hg)) bar_arrive(2, 256);
                if (hp) bar_arrive(14, 384);
                const float (&oa)[4] = o[hp * 6 + 2], (&ob)[4] = o[hp * 6 + 5];
                const float hl = rcp(low ? ob[0] : oa[0]) * g0, hh = rcp(low ? ob[2] : oa[2]) * g1;
                const float gl = __shfl_xor_sync(0xffffffffu, hl, 2), gh = __shfl_xor_sync(0xffffffffu, hh, 2);
                const float ial = low ? gl : hl, iah = low ? gh : hh, ibl = low ? hl : gl, ibh = low ? hh : gh;
#pragma unroll
                for (int i = 0; i < 2; i++) {
                    ol[hp * 5 + i] = pack2(o[hp * 6 + i][0] * ial, o[hp * 6 + i][1] * ial);
                    oh[hp * 5 + i] = pack2(o[hp * 6 + i][2] * iah, o[hp * 6 + i][3] * iah);
                    ol[hp * 5 + 3 + i] = pack2(o[hp * 6 + 3 + i][0] * ibl, o[hp * 6 + 3 + i][1] * ibl);
                    oh[hp * 5 + 3 + i] = pack2(o[hp * 6 + 3 + i][2] * ibh, o[hp * 6 + 3 + i][3] * ibh);
                }
                ol[hp * 5 + 2] = pack2((low ? oa[0] : ob[0]) * gl, (low ? oa[1] : ob[1]) * gl);
                oh[hp * 5 + 2] = pack2((low ? oa[2] : ob[2]) * gh, (low ? oa[3] : ob[3]) * gh);
#pragma unroll
                for (int t = hp * 5; t < hp * 5 + 5; t++) {
                    st_relaxed4(po + t * 32, ol[t]);
                    st_relaxed4(po + 320 + t * 32, oh[t]);
                }
            }
        }
        TS(warp == 0 ? 5 : warp == 4 ? 21 : warp == 5 ? 29 : warp == 1 ? 31 : 63);
        const uint4* ow = sc + (SC_O + HALF(hg) * 640 - hg * SC_SIZE);
        if (wg != HALF(hg)) {
            mbar_wait(RS_POS ? B_ALL : B_INIT, 0);
            mbar_wait(B_EMPTY + 3 * 8, 0);
            if (w4 < 2) bar_arrive(9, 256); else bar_sync(9, 256);
            mbar_wait(B_GUD, 0);
            if (w4 == 0) TS(wg ? 26 : 27);
            uint32_t ph = 0;
#pragma unroll 1
            for (int i = w4 + 1 + NRS; i < 8; i += 4) {
                const uint4* src = ow + src_of(i, hg) * SC_SIZE;
                const uint32_t buf = o_buf(i), chk = buf + lane * 132;
                if (i < 5 + NRS) {
                    while (__any_sync(0xffffffffu, ld_relaxed4(&src[(lane & 3) * 160 + 159].w) == SENT)) {}
                    if (w4) pace(clock(), w4 * O_DT - O_D);
                } else {
                    mbar_wait(B_OE + (i - 4) * 8, 0);
                }
                if (i == 1 + NRS) TS(wg ? 3 : 4);
                uint32_t c;
                do {
                    if (elect_one()) {
                        mbar_expect_tx(B_OT + w4 * 8, 10240);
                        bulk_load(buf, src, 10240, B_OT + w4 * 8);
                    }
                    mbar_wait(B_OT + w4 * 8, ph);
                    if (i == 1 + NRS && !ph) TS(wg ? 19 : 20);
                    ph ^= 1;
                    c = max(max(lds4(chk), lds4(chk + 4096)), lds4(chk + 6144));
                } while (__any_sync(0xffffffffu, c == SENT));
                if (lane == 0) mbar_arrive(B_G2 + i * 8);
                TS(32 + i);
            }
            return;
        }

        float oc[80];
        bar_arrive(9, 256);
        bar_sync(2, 256);
        mbar_wait(B_G2, 0);
        TS(w4 == 0 ? 6 : 63);
        wg_fence();
#pragma unroll
        for (int s = 0; s < 5; s++)
            wgmma_own(oc, ol[2 * s], oh[2 * s], ol[2 * s + 1], oh[2 * s + 1], desc_lo(wo_buf(0), 10240) + s * 128, s);
        wg_commit();
        mbar_wait(B_XS, 0);
        const int orow = p0 + wg * 64 + w4 * 16;
        const uint32_t tk1 = ~lds4(SM_KEY + 16 * 4) & 2047, tk2 = ~lds4(SM_KEY + 17 * 4) & 2047;
        const uint32_t sel1 = (tk1 & 1) == par ? (tk1 >> 1) - orow : 99, sel2 = (tk2 & 1) == par ? (tk2 >> 1) - orow : 99;
        const uint32_t n0 = pack2(1.f - g0, 1.f - g0), n1 = pack2(1.f - g1, 1.f - g1);
        const uint32_t stg = SM_OUT + w4 * 5120;
        const uint32_t m128 = keep(stg + (lane & 15) * 128 + (((lane >> 4) ^ (lane & 7)) << 4));
        const uint32_t m64 = keep(stg + 4096 + (lane & 15) * 64 + (((lane >> 4) ^ ((lane >> 1) & 3)) << 4));
        const uint32_t l128 = keep(stg + (lane >> 3) * 128 + (((lane & 7) ^ (lane >> 3)) << 4));
        const uint32_t l64 = keep(stg + 4096 + r * 64 + ((cq ^ (lane >> 3)) << 4));
        char* const o128 = reinterpret_cast<char*>(P.op) + keep(((orow + (lane >> 3)) * 2 + par) * 1280 + kba * 128 + (lane & 7) * 16);
        char* const o64 = reinterpret_cast<char*>(P.op) + keep(((orow + r) * 2 + par) * 1280 + kbr * 128 + odd * 64 + cq * 16);
        if (RS_POS == 0) mbar_wait(B_INIT, 0);
        wg_wait<0>();
        if (leader) mbar_arrive(B_OE);
        {
            uint32_t af[NRS][20];
            uint32_t m;
            do {
#pragma unroll
                for (int i = 0; i < NRS; i++) {
                    const uint32_t* p = reinterpret_cast<const uint32_t*>(ow + src_of(i + 1, hg) * SC_SIZE + w4 * 160) + lane;
#pragma unroll
                    for (int t = 0; t < 20; t++) af[i][t] = ld_relaxed4(p + t * 32);
                }
                m = 0;
#pragma unroll
                for (int i = 0; i < NRS; i++)
#pragma unroll
                    for (int t = 0; t < 20; t++) m = max(m, af[i][t]);
            } while (__any_sync(0xffffffffu, m == SENT));
#pragma unroll
            for (int i = 0; i < NRS; i++) {
                mbar_wait(B_G2 + 8 + i * 8, 0);
                TS(w4 == 0 ? (i ? 11 : 7) : 63);
                wg_fence();
#pragma unroll
                for (int s = 0; s < 5; s++)
                    wgmma_own(oc, af[i][2 * s], af[i][10 + 2 * s], af[i][2 * s + 1], af[i][11 + 2 * s], desc_lo(wo_buf(i + 1), 10240) + s * 128, 1);
                wg_commit();
            }
            if (NRS == 2) {
                wg_wait<1>();
                if (leader) mbar_arrive(B_OE + 8);
            }
        }
#pragma unroll 1
        for (int i = 1 + NRS; i < 8; i++) {
            const uint32_t ao = desc_lo(0, 128) + (o_buf(i) >> 4), wo = desc_lo(0, 10240) + (wo_buf(i) >> 4);
            mbar_wait(B_G2 + i * 8, 0);
            TS(w4 == 0 ? (i < 2 ? 6 + i : i < 7 ? 9 + i : 17) : 63);
            wg_fence();
#pragma unroll
            for (int s = 0; s < 5; s++) wgmma_out(oc, ao + s * 16, wo + s * 128, 1);
            wg_commit();
            if (i < 5) {
                wg_wait<1>();
                if (i > 1 && leader) mbar_arrive(B_OE - 8 + i * 8);
            }
        }
        TS(w4 == 0 ? 8 : 63);

        if (min(sel1, sel2) < 16) {
            mbar_wait(B_MOD, 0);
#pragma unroll 1
            for (int j = 0; j < 2; j++) {
                const uint32_t sel = j ? sel2 : sel1;
#pragma unroll
                for (int t = 0; t < 20; t++) {
                    const uint32_t u = lds4(SM_U + j * 320 + cq * 4 + (t < 16 ? odd * 64 + t * 16 : (odd ? 0 : 256) + (t - 16) * 16));
                    if (sel == r) nb[2 * t] = hadd2(nb[2 * t], u);
                    if (sel == r + 8) nb[2 * t + 1] = hadd2(nb[2 * t + 1], u);
                }
            }
        }
        wg_wait<0>();
        TS(w4 == 0 ? 9 : 63);
        const bool nan = oc[0] != oc[0] || oc[2] != oc[2];
#pragma unroll
        for (int part = 0; part < 3; part++) {
            const int s0 = part ? part * 4 - 4 : 8, ns = part ? 4 : 2;
#pragma unroll
            for (int i = 0; i < 4; i++) {
                if (i >= ns) break;
                const int s = s0 + i;
                const uint32_t y0 = hfma2(n0, nb[s * 4], pack2(oc[s * 8 + 0], oc[s * 8 + 1]));
                const uint32_t y1 = hfma2(n1, nb[s * 4 + 1], pack2(oc[s * 8 + 2], oc[s * 8 + 3]));
                const uint32_t y2 = hfma2(n0, nb[s * 4 + 2], pack2(oc[s * 8 + 4], oc[s * 8 + 5]));
                const uint32_t y3 = hfma2(n1, nb[s * 4 + 3], pack2(oc[s * 8 + 6], oc[s * 8 + 7]));
                asm volatile("stmatrix.sync.aligned.m8n8.x4.shared.b16 [%0], {%1,%2,%3,%4};"
                             ::"r"(((s < 8 ? m128 : m64) ^ ((s & 3) * 32)) + (s & 4) * 512), "r"(y0), "r"(y1), "r"(y2), "r"(y3) : "memory");
            }
            __syncwarp();
            uint4 v[4];
#pragma unroll
            for (int i = 0; i < 4; i++)
                if (i < ns) v[i] = lds16(!part ? l64 + i * 512 : (l128 ^ ((i & 1) * 64)) + i * 512 + s0 * 512);
#pragma unroll
            for (int i = 0; i < 4; i++)
                if (i < ns) *reinterpret_cast<uint4*>(!part ? o64 + i * 8 * 2560 : o128 + i * 4 * 2560 + s0 * 32) = v[i];
            if (part == 0) TS(w4 == 0 ? 1 : 63);
        }
        TS(w4 == 0 ? 10 : 63);
        if (lane == 0) mbar_arrive(B_DONE);
        uint32_t redo;
        asm volatile("{\n.reg .pred p, q;\nsetp.ne.u32 p, %1, 0;\nbar.cta.red.or.pred q, 10, 128, p;\nselp.u32 %0, 1, 0, q;\n}"
                     : "=r"(redo) : "r"((uint32_t)nan) : "memory");
        if (redo) {
            const int cb = CB(hg);
#pragma unroll 1
            for (int i = 0; i < 8; i++) {
                if (leader) {
                    mbar_expect_tx(B_RE, 25600);
                    tma_3d(SM_W, &P.woa, B_RE, 0, i * 80, (cb * 5 + 1) >> 1);
                    tma_2d(SM_W + 20480, &P.wob, B_RE, cb * 160 + ((cb & 1) ? 0 : 128), i * 80);
                }
#pragma unroll 1
                for (int s = 0; s < 20; s++) {
                    const int w = w4 * 640 + s * 32 + lane;
                    uint32_t v, it = 0;
                    do {
                        v = ld_relaxed4(reinterpret_cast<const uint32_t*>(ow + i * SC_SIZE) + w);
                        if (++it > (1u << 22)) fault();
                    } while ((v >> 16) == 0xFFFFu || (v & 0xFFFFu) == 0xFFFFu);
                    sts4(SM_X + w * 4, v);
                }
                fence_async_smem();
                __syncwarp();
                bar_sync(10, 128);
                mbar_wait(B_RE, i & 1);
                wg_fence();
#pragma unroll
                for (int s = 0; s < 5; s++) wgmma_out(oc, desc_lo(SM_X, 128) + s * 16, desc_lo(SM_W, 10240) + s * 128, s || i);
                wg_commit();
                wg_wait<0>();
                bar_sync(10, 128);
            }
#pragma unroll
            for (int t = 0; t < 40; t++) {
                const int col = (t < 32 ? kba * 64 + (t >> 1) * 8 : kbr * 64 + odd * 32 + ((t - 32) >> 1) * 8) + cq * 2;
                *reinterpret_cast<uint32_t*>(P.op + ((orow + r + (t & 1) * 8) * 2 + par) * 640 + col) =
                    hfma2((t & 1) ? n1 : n0, nb[t], pack2(oc[2 * t], oc[2 * t + 1]));
            }
        }
    }
}

typedef CUresult (*EncodeFn)(CUtensorMap*, CUtensorMapDataType, cuuint32_t, void*, const cuuint64_t*, const cuuint64_t*,
                             const cuuint32_t*, const cuuint32_t*, CUtensorMapInterleave, CUtensorMapSwizzle,
                             CUtensorMapL2promotion, CUtensorMapFloatOOBfill);

void encode(EncodeFn fn, CUtensorMap* m, const void* ptr, int rank, const cuuint64_t* dims, const cuuint64_t* strides,
            const cuuint32_t* box, CUtensorMapSwizzle swz) {
    const cuuint32_t es[4] = {1, 1, 1, 1};
    fn(m, CU_TENSOR_MAP_DATA_TYPE_BFLOAT16, rank, const_cast<void*>(ptr), dims, strides, box, es,
       CU_TENSOR_MAP_INTERLEAVE_NONE, swz, CU_TENSOR_MAP_L2_PROMOTION_L2_128B, CU_TENSOR_MAP_FLOAT_OOB_FILL_NONE);
}

}

extern "C" void kernel_launch(void* const* d_in, const int* in_sizes, int n_in, void* d_out, int out_size) {
    (void)in_sizes; (void)n_in; (void)out_size;
    Params P;
    P.xp = (const __nv_bfloat16*)d_in[0];
    P.wop = (const __nv_bfloat16*)d_in[2];
    P.gp = (const __nv_bfloat16*)d_in[5];
    P.upp = (const __nv_bfloat16*)d_in[6];
    P.op = (__nv_bfloat16*)d_out;
    P.w_r = (const __nv_bfloat16*)d_in[4];
    P.gate_w = (const __nv_bfloat16*)d_in[8];

    void* fp = nullptr;
    cudaDriverEntryPointQueryResult st;
    cudaGetDriverEntryPoint("cuTensorMapEncodeTiled", &fp, cudaEnableDefault, &st);
    EncodeFn fn = (EncodeFn)fp;
    const cuuint64_t xd[3] = {640, 2, 1024}, xs[2] = {1280, 2560};
    const cuuint32_t bx[3] = {64, 1, 64}, bx2[3] = {64, 1, 128};
    encode(fn, &P.x2, d_in[0], 3, xd, xs, bx2, CU_TENSOR_MAP_SWIZZLE_128B);
    encode(fn, &P.x, d_in[0], 3, xd, xs, bx, CU_TENSOR_MAP_SWIZZLE_128B);
    const cuuint64_t wd[3] = {640, 640, 3}, ws[2] = {3840, 1280};
    const cuuint32_t bw[3] = {64, 32, 3}, bwr[3] = {16, 32, 3};
    encode(fn, &P.w, d_in[1], 3, wd, ws, bw, CU_TENSOR_MAP_SWIZZLE_128B);
    encode(fn, &P.wr, d_in[1], 3, wd, ws, bwr, CU_TENSOR_MAP_SWIZZLE_32B);
    const cuuint64_t ad[3] = {64, 640, 10}, as[2] = {1280, 128}, bd[2] = {640, 640};
    const cuuint32_t ba[3] = {64, 80, 2}, bb[2] = {32, 80};
    encode(fn, &P.woa, d_in[2], 3, ad, as, ba, CU_TENSOR_MAP_SWIZZLE_128B);
    encode(fn, &P.wob, d_in[2], 2, bd, as, bb, CU_TENSOR_MAP_SWIZZLE_128B);
    const cuuint64_t gd[2] = {1728, 640}, gs[1] = {3456}, dd[3] = {64, 1728, 10};
    const cuuint32_t bg[2] = {64, 80 / GH_N}, bu[2] = {64, 160}, bdn[3] = {64, DN_K ? 8 : 32, DN_K ? 3 : 1}, bxg[3] = {64, 1, 16};
    encode(fn, &P.xg, d_in[0], 3, xd, xs, bxg, CU_TENSOR_MAP_SWIZZLE_128B);
    encode(fn, &P.gate, d_in[5], 2, gd, gs, bg, CU_TENSOR_MAP_SWIZZLE_128B);
    encode(fn, &P.up, d_in[6], 2, gd, gs, bu, CU_TENSOR_MAP_SWIZZLE_128B);
    encode(fn, &P.down, d_in[7], 3, dd, as, bdn, CU_TENSOR_MAP_SWIZZLE_128B);

    cudaFuncSetAttribute(fused_kernel, cudaFuncAttributeMaxDynamicSharedMemorySize, SM_TOTAL);
    fused_kernel<<<NCTA, 512, SM_TOTAL, cudaStreamPerThread>>>(P);
}
```

```cpp
#include <cuda_runtime.h>
#include <cuda_bf16.h>
#include <cuda.h>
#include <stdint.h>

namespace {

constexpr int NCTA = 128;
constexpr int NFFN = 108;
constexpr uint32_t SENT = 0xFFFFFFFFu;

constexpr uint32_t SB = 1024;
constexpr uint32_t SM_W = SB;
constexpr uint32_t SM_X = SB + 122880;
constexpr uint32_t SM_F = SB + 188416;
constexpr uint32_t SM_G = SB + 212992;
constexpr uint32_t SM_BAR = SB + 223232;
constexpr uint32_t SM_PROF = SB + 223744;
constexpr uint32_t SM_KEY = SB + 224000;
constexpr uint32_t SM_RED = SB + 224128;
constexpr uint32_t SM_XS = SB + 226688;
constexpr uint32_t SM_SENT = SB + 227328;
constexpr uint32_t SM_U = SM_RED + 1920;
constexpr uint32_t SM_GATE = SM_RED;
constexpr uint32_t SM_TOTAL = 232448;
constexpr uint32_t SM_HALO1 = SM_X + 30720;
constexpr uint32_t SM_HALO = SM_HALO1 + 12800;
constexpr uint32_t SM_UP = SM_W + 61440;
constexpr uint32_t SM_DN = SM_UP + 6144;
constexpr uint32_t SM_Y = SM_F + 26624;
constexpr uint32_t SM_OUT = SM_W + 92160;

constexpr uint32_t B_XL0 = SM_BAR, B_FULL = SM_BAR + 8, B_GT = SM_BAR + 72, B_RG = SM_BAR + 80, B_RG2 = SM_BAR + 88,
                   B_XS = SM_BAR + 96, B_EMPTY = SM_BAR + 128, B_DONE = SM_BAR + 192, B_XE = SM_BAR + 200,
                   B_GUD = SM_BAR + 224, B_OE = B_GUD + 8, B_OT = B_GUD + 40, B_MOD = B_GUD + 72,
                   B_GU = SM_BAR + 104, B_ALL = SM_BAR + 112, B_UP = SM_BAR + 120, B_DN = B_GUD + 80, B_RS = B_GUD + 88, B_INIT = B_GUD + 96,
                   B_RE = B_GUD + 104, B_G2 = B_GUD + 112, B_DD = B_GUD + 176, B_HF = B_GUD + 184;

struct Params {
    CUtensorMap x, x2, w, wr, woa, wob, xg, gate, up, up2, down;
    __nv_bfloat16* op;
    const __nv_bfloat16 *xp, *upp, *w_r, *gate_w;
};

constexpr int SC_O = 0;
constexpr int SC_HALO = 1280;
constexpr int SC_GU = 1440;
constexpr int SC_Y = 1504;
constexpr int SC_SIZE = 1600;
__device__ __align__(128) uint4 g_sc[NCTA * SC_SIZE];
__device__ __align__(128) uint4 g_cand[NCTA];
__device__ __align__(16) uint32_t g_gate[2048];
__device__ __align__(128) unsigned g_cnt[64];
#define TSM(i) do { } while (0)
#define TS(i) do { } while (0)
#define TS2(i) do { } while (0)
#define TSX(i) do { } while (0)

__device__ __forceinline__ uint32_t smem_u32(const void* p) { return (uint32_t)__cvta_generic_to_shared(p); }
__device__ __forceinline__ void fault() { asm volatile("st.shared.u32 [%0], %0;" ::"r"(0x100001) : "memory"); }
__device__ __forceinline__ void mbar_init(uint32_t bar, uint32_t cnt) {
    asm volatile("mbarrier.init.shared::cta.b64 [%0], %1;" ::"r"(bar), "r"(cnt) : "memory");
}
__device__ __forceinline__ void mbar_expect_tx(uint32_t bar, uint32_t bytes) {
    asm volatile("mbarrier.arrive.expect_tx.shared::cta.b64 _, [%0], %1;" ::"r"(bar), "r"(bytes) : "memory");
}
__device__ __forceinline__ void mbar_arrive(uint32_t bar) {
    asm volatile("mbarrier.arrive.shared::cta.b64 _, [%0];" ::"r"(bar) : "memory");
}
__device__ __forceinline__ bool mbar_try(uint32_t bar, uint32_t parity) {
    uint32_t ok;
    asm volatile("{\n.reg .pred p;\nmbarrier.try_wait.parity.shared::cta.b64 p, [%1], %2;\nselp.u32 %0, 1, 0, p;\n}"
                 : "=r"(ok) : "r"(bar), "r"(parity) : "memory");
    return ok;
}
__device__ __forceinline__ void mbar_wait(uint32_t bar, uint32_t parity) {
    asm volatile("{\n.reg .pred p;\nAGAIN:\nmbarrier.try_wait.parity.shared::cta.b64 p, [%0], %1;\n@!p bra AGAIN;\n}"
                 ::"r"(bar), "r"(parity) : "memory");
}
__device__ __forceinline__ void tma_2d(uint32_t dst, const CUtensorMap* m, uint32_t bar, int c0, int c1) {
    asm volatile("cp.async.bulk.tensor.2d.shared::cluster.global.mbarrier::complete_tx::bytes [%0], [%1, {%3, %4}], [%2];"
                 ::"r"(dst), "l"(m), "r"(bar), "r"(c0), "r"(c1) : "memory");
}
__device__ __forceinline__ void bulk_load(uint32_t dst, const void* src, uint32_t bytes, uint32_t bar) {
    asm volatile("cp.async.bulk.shared::cluster.global.mbarrier::complete_tx::bytes [%0], [%1], %2, [%3];"
                 ::"r"(dst), "l"(src), "r"(bytes), "r"(bar) : "memory");
}
__device__ __forceinline__ void bulk_store(void* dst, uint32_t src, uint32_t bytes) {
    asm volatile("cp.async.bulk.global.shared::cta.bulk_group [%0], [%1], %2;" ::"l"(dst), "r"(src), "r"(bytes) : "memory");
}
__device__ __forceinline__ void tma_3d(uint32_t dst, const CUtensorMap* m, uint32_t bar, int c0, int c1, int c2) {
    asm volatile("cp.async.bulk.tensor.3d.shared::cluster.global.mbarrier::complete_tx::bytes [%0], [%1, {%3, %4, %5}], [%2];"
                 ::"r"(dst), "l"(m), "r"(bar), "r"(c0), "r"(c1), "r"(c2) : "memory");
}
__device__ __forceinline__ void fence_async_smem() { asm volatile("fence.proxy.async.shared::cta;" ::: "memory"); }
__device__ __forceinline__ void wg_fence() { asm volatile("wgmma.fence.sync.aligned;" ::: "memory"); }
__device__ __forceinline__ void wg_commit() { asm volatile("wgmma.commit_group.sync.aligned;" ::: "memory"); }
template <int N> __device__ __forceinline__ void wg_wait() { asm volatile("wgmma.wait_group.sync.aligned %0;" ::"n"(N) : "memory"); }
__device__ __forceinline__ void bar_sync(int id, int n) { asm volatile("bar.cta.sync %0, %1;" ::"r"(id), "r"(n) : "memory"); }
__device__ __forceinline__ void bar_arrive(int id, int n) { asm volatile("bar.cta.arrive %0, %1;" ::"r"(id), "r"(n) : "memory"); }

__device__ constexpr uint32_t desc_lo(uint32_t addr, uint32_t lbo) { return (addr >> 4) | ((lbo >> 4) << 16); }
__device__ __forceinline__ bool elect_one() {
    uint32_t p;
    asm volatile("{\n.reg .pred p;\nelect.sync _|p, 0xffffffff;\nselp.u32 %0, 1, 0, p;\n}" : "=r"(p));
    return p;
}
__device__ __forceinline__ uint32_t ld_relaxed4(const void* p) {
    uint32_t v;
    asm volatile("ld.relaxed.gpu.global.u32 %0, [%1];" : "=r"(v) : "l"(p) : "memory");
    return v;
}
__device__ __forceinline__ void st_relaxed4(void* p, uint32_t v) {
    asm volatile("st.relaxed.gpu.global.u32 [%0], %1;" ::"l"(p), "r"(v) : "memory");
}
__device__ __forceinline__ void red_inc(unsigned* p, unsigned after) {
    asm volatile("red.relaxed.gpu.global.add.u32 [%0], 1;" ::"l"(p), "r"(after) : "memory");
}
__device__ __forceinline__ uint32_t lds4(uint32_t a) {
    uint32_t v;
    asm volatile("ld.shared.u32 %0, [%1];" : "=r"(v) : "r"(a) : "memory");
    return v;
}
__device__ __forceinline__ void sts4(uint32_t a, uint32_t v) { asm volatile("st.shared.u32 [%0], %1;" ::"r"(a), "r"(v) : "memory"); }
__device__ __forceinline__ uint32_t hadd2(uint32_t a, uint32_t b) {
    uint32_t d;
    asm("add.rn.bf16x2 %0, %1, %2;" : "=r"(d) : "r"(a), "r"(b));
    return d;
}
__device__ __forceinline__ uint32_t hfma2(uint32_t a, uint32_t b, uint32_t c) {
    uint32_t d;
    asm("fma.rn.bf16x2 %0, %1, %2, %3;" : "=r"(d) : "r"(a), "r"(b), "r"(c));
    return d;
}
__device__ __forceinline__ uint4 ld_relaxed16(const void* p) {
    uint4 v;
    asm volatile("{\n.reg .b128 t;\n.reg .b64 lo, hi;\nld.relaxed.gpu.global.b128 t, [%4];\nmov.b128 {lo, hi}, t;\n"
                 "mov.b64 {%0, %1}, lo;\nmov.b64 {%2, %3}, hi;\n}" : "=r"(v.x), "=r"(v.y), "=r"(v.z), "=r"(v.w) : "l"(p) : "memory");
    return v;
}
__device__ __forceinline__ void st_relaxed16(void* p, uint32_t a, uint32_t b, uint32_t c, uint32_t d) {
    uint64_t lo = (uint64_t)a | ((uint64_t)b << 32), hi = (uint64_t)c | ((uint64_t)d << 32);
    asm volatile("{\n.reg .b128 t;\nmov.b128 t, {%1, %2};\nst.relaxed.gpu.global.b128 [%0], t;\n}" ::"l"(p), "l"(lo), "l"(hi) : "memory");
}
__device__ __forceinline__ uint4 lds16(uint32_t a) {
    uint4 v;
    asm volatile("ld.shared.v4.u32 {%0, %1, %2, %3}, [%4];" : "=r"(v.x), "=r"(v.y), "=r"(v.z), "=r"(v.w) : "r"(a) : "memory");
    return v;
}
__device__ __forceinline__ void sts16(uint32_t a, uint32_t x, uint32_t y, uint32_t z, uint32_t w) {
    asm volatile("st.shared.v4.u32 [%0], {%1, %2, %3, %4};" ::"r"(a), "r"(x), "r"(y), "r"(z), "r"(w) : "memory");
}
__device__ __forceinline__ uint32_t pack2(float lo, float hi) {
    uint32_t r;
    asm("cvt.rn.bf16x2.f32 %0, %1, %2;" : "=r"(r) : "f"(hi), "f"(lo));
    return r;
}
__device__ __forceinline__ uint32_t pack2v(float lo, float hi) {
    uint32_t r;
    asm volatile("cvt.rn.bf16x2.f32 %0, %1, %2;" : "=r"(r) : "f"(hi), "f"(lo));
    return r;
}
__device__ __forceinline__ uint32_t shl(uint32_t v, uint32_t n) {
    uint32_t r;
    asm("shl.b32 %0, %1, %2;" : "=r"(r) : "r"(v), "r"(n));
    return r;
}
__device__ __forceinline__ float bf_lo(uint32_t u) { return __uint_as_float(u << 16); }
__device__ __forceinline__ float bf_hi(uint32_t u) { return __uint_as_float(u & 0xFFFF0000u); }
__device__ __forceinline__ float bf_round(float f) { return __bfloat162float(__float2bfloat16_rn(f)); }
__device__ __forceinline__ uint32_t movm(uint32_t a) {
    uint32_t d;
    asm volatile("movmatrix.sync.aligned.m8n8.trans.b16 %0, %1;" : "=r"(d) : "r"(a));
    return d;
}
__device__ __forceinline__ void mma16(float (&c)[4], uint32_t a0, uint32_t a1, uint32_t a2, uint32_t a3, uint32_t b0, uint32_t b1) {
    asm volatile("mma.sync.aligned.m16n8k16.row.col.f32.bf16.bf16.f32 {%0,%1,%2,%3}, {%4,%5,%6,%7}, {%8,%9}, {%0,%1,%2,%3};"
                 : "+f"(c[0]), "+f"(c[1]), "+f"(c[2]), "+f"(c[3]) : "r"(a0), "r"(a1), "r"(a2), "r"(a3), "r"(b0), "r"(b1));
}
__device__ __forceinline__ void mma8(float (&c)[4], uint32_t a0, uint32_t a1, uint32_t b0) {
    asm volatile("mma.sync.aligned.m16n8k8.row.col.f32.bf16.bf16.f32 {%0,%1,%2,%3}, {%4,%5}, {%6}, {%0,%1,%2,%3};"
                 : "+f"(c[0]), "+f"(c[1]), "+f"(c[2]), "+f"(c[3]) : "r"(a0), "r"(a1), "r"(b0));
}
__device__ __forceinline__ float ex2(float x) { float y; asm("ex2.approx.ftz.f32 %0, %1;" : "=f"(y) : "f"(x)); return y; }
__device__ __forceinline__ float rcp(float x) { float y; asm("rcp.approx.ftz.f32 %0, %1;" : "=f"(y) : "f"(x)); return y; }
__device__ __forceinline__ float sigmoidf(float z) { return rcp(1.0f + ex2(z * -1.4426950408889634f)); }
__device__ __forceinline__ float u2f(uint32_t u) { return __uint_as_float(u); }
__device__ __forceinline__ uint32_t f2u(float f) { return __float_as_uint(f); }

__device__ __forceinline__ void wgmma_main(float (&d)[96], uint32_t a, uint32_t b, int scale_d) {
    asm volatile("{\n.reg .pred p;\n.reg .b64 da, db;\nsetp.ne.b32 p, %98, 0;\n"
        "mov.b64 da, {%96, 0x40000040};\nmov.b64 db, {%97, 0x40000040};\n"
        "wgmma.mma_async.sync.aligned.m64n192k16.f32.bf16.bf16 "
        "{%0, %1, %2, %3, %4, %5, %6, %7, %8, %9, %10, %11, %12, %13, %14, %15, "
        "%16, %17, %18, %19, %20, %21, %22, %23, %24, %25, %26, %27, %28, %29, %30, %31, "
        "%32, %33, %34, %35, %36, %37, %38, %39, %40, %41, %42, %43, %44, %45, %46, %47, "
        "%48, %49, %50, %51, %52, %53, %54, %55, %56, %57, %58, %59, %60, %61, %62, %63, "
        "%64, %65, %66, %67, %68, %69, %70, %71, %72, %73, %74, %75, %76, %77, %78, %79, "
        "%80, %81, %82, %83, %84, %85, %86, %87, %88, %89, %90, %91, %92, %93, %94, %95}, "
        "da, db, p, 1, 1, 0, 1;\n}\n"
        : "+f"(d[0]), "+f"(d[1]), "+f"(d[2]), "+f"(d[3]), "+f"(d[4]), "+f"(d[5]), "+f"(d[6]), "+f"(d[7]),
          "+f"(d[8]), "+f"(d[9]), "+f"(d[10]), "+f"(d[11]), "+f"(d[12]), "+f"(d[13]), "+f"(d[14]), "+f"(d[15]),
          "+f"(d[16]), "+f"(d[17]), "+f"(d[18]), "+f"(d[19]), "+f"(d[20]), "+f"(d[21]), "+f"(d[22]), "+f"(d[23]),
          "+f"(d[24]), "+f"(d[25]), "+f"(d[26]), "+f"(d[27]), "+f"(d[28]), "+f"(d[29]), "+f"(d[30]), "+f"(d[31]),
          "+f"(d[32]), "+f"(d[33]), "+f"(d[34]), "+f"(d[35]), "+f"(d[36]), "+f"(d[37]), "+f"(d[38]), "+f"(d[39]),
          "+f"(d[40]), "+f"(d[41]), "+f"(d[42]), "+f"(d[43]), "+f"(d[44]), "+f"(d[45]), "+f"(d[46]), "+f"(d[47]),
          "+f"(d[48]), "+f"(d[49]), "+f"(d[50]), "+f"(d[51]), "+f"(d[52]), "+f"(d[53]), "+f"(d[54]), "+f"(d[55]),
          "+f"(d[56]), "+f"(d[57]), "+f"(d[58]), "+f"(d[59]), "+f"(d[60]), "+f"(d[61]), "+f"(d[62]), "+f"(d[63]),
          "+f"(d[64]), "+f"(d[65]), "+f"(d[66]), "+f"(d[67]), "+f"(d[68]), "+f"(d[69]), "+f"(d[70]), "+f"(d[71]),
          "+f"(d[72]), "+f"(d[73]), "+f"(d[74]), "+f"(d[75]), "+f"(d[76]), "+f"(d[77]), "+f"(d[78]), "+f"(d[79]),
          "+f"(d[80]), "+f"(d[81]), "+f"(d[82]), "+f"(d[83]), "+f"(d[84]), "+f"(d[85]), "+f"(d[86]), "+f"(d[87]),
          "+f"(d[88]), "+f"(d[89]), "+f"(d[90]), "+f"(d[91]), "+f"(d[92]), "+f"(d[93]), "+f"(d[94]), "+f"(d[95])
        : "r"(a), "r"(b), "r"(scale_d));
}

__device__ __forceinline__ void wgmma_rem(float (&d)[24], uint32_t a, uint32_t b, int scale_d) {
    asm volatile("{\n.reg .pred p;\n.reg .b64 da, db;\nsetp.ne.b32 p, %26, 0;\n"
        "mov.b64 da, {%24, 0x40000040};\nmov.b64 db, {%25, 0xC0000010};\n"
        "wgmma.mma_async.sync.aligned.m64n48k16.f32.bf16.bf16 "
        "{%0, %1, %2, %3, %4, %5, %6, %7, %8, %9, %10, %11, %12, %13, %14, %15, "
        "%16, %17, %18, %19, %20, %21, %22, %23}, "
        "da, db, p, 1, 1, 0, 1;\n}\n"
        : "+f"(d[0]), "+f"(d[1]), "+f"(d[2]), "+f"(d[3]), "+f"(d[4]), "+f"(d[5]), "+f"(d[6]), "+f"(d[7]),
          "+f"(d[8]), "+f"(d[9]), "+f"(d[10]), "+f"(d[11]), "+f"(d[12]), "+f"(d[13]), "+f"(d[14]), "+f"(d[15]),
          "+f"(d[16]), "+f"(d[17]), "+f"(d[18]), "+f"(d[19]), "+f"(d[20]), "+f"(d[21]), "+f"(d[22]), "+f"(d[23])
        : "r"(a), "r"(b), "r"(scale_d));
}

__device__ __forceinline__ void wgmma_out64(float (&d)[80], uint32_t a, uint32_t b, int scale_d) {
    asm volatile("{\n.reg .pred p;\n.reg .b64 da, db;\nsetp.ne.b32 p, %34, 0;\n"
        "mov.b64 da, {%32, 0x50};\nmov.b64 db, {%33, 0x40000040};\n"
        "wgmma.mma_async.sync.aligned.m64n64k16.f32.bf16.bf16 "
        "{%0, %1, %2, %3, %4, %5, %6, %7, %8, %9, %10, %11, %12, %13, %14, %15, "
        "%16, %17, %18, %19, %20, %21, %22, %23, %24, %25, %26, %27, %28, %29, %30, %31}, "
        "da, db, p, 1, 1, 0, 1;\n}\n"
        : "+f"(d[0]), "+f"(d[1]), "+f"(d[2]), "+f"(d[3]), "+f"(d[4]), "+f"(d[5]), "+f"(d[6]), "+f"(d[7]),
          "+f"(d[8]), "+f"(d[9]), "+f"(d[10]), "+f"(d[11]), "+f"(d[12]), "+f"(d[13]), "+f"(d[14]), "+f"(d[15]),
          "+f"(d[16]), "+f"(d[17]), "+f"(d[18]), "+f"(d[19]), "+f"(d[20]), "+f"(d[21]), "+f"(d[22]), "+f"(d[23]),
          "+f"(d[24]), "+f"(d[25]), "+f"(d[26]), "+f"(d[27]), "+f"(d[28]), "+f"(d[29]), "+f"(d[30]), "+f"(d[31])
        : "r"(a), "r"(b), "r"(scale_d));
}
__device__ __forceinline__ void wgmma_out96(float (&d)[80], uint32_t a, uint32_t b, int scale_d) {
    asm volatile("{\n.reg .pred p;\n.reg .b64 da, db;\nsetp.ne.b32 p, %50, 0;\n"
        "mov.b64 da, {%48, 0x50};\nmov.b64 db, {%49, 0x40000040};\n"
        "wgmma.mma_async.sync.aligned.m64n96k16.f32.bf16.bf16 "
        "{%0, %1, %2, %3, %4, %5, %6, %7, %8, %9, %10, %11, %12, %13, %14, %15, "
        "%16, %17, %18, %19, %20, %21, %22, %23, %24, %25, %26, %27, %28, %29, %30, %31, "
        "%32, %33, %34, %35, %36, %37, %38, %39, %40, %41, %42, %43, %44, %45, %46, %47}, "
        "da, db, p, 1, 1, 0, 1;\n}\n"
        : "+f"(d[32]), "+f"(d[33]), "+f"(d[34]), "+f"(d[35]), "+f"(d[36]), "+f"(d[37]), "+f"(d[38]), "+f"(d[39]),
          "+f"(d[40]), "+f"(d[41]), "+f"(d[42]), "+f"(d[43]), "+f"(d[44]), "+f"(d[45]), "+f"(d[46]), "+f"(d[47]),
          "+f"(d[48]), "+f"(d[49]), "+f"(d[50]), "+f"(d[51]), "+f"(d[52]), "+f"(d[53]), "+f"(d[54]), "+f"(d[55]),
          "+f"(d[56]), "+f"(d[57]), "+f"(d[58]), "+f"(d[59]), "+f"(d[60]), "+f"(d[61]), "+f"(d[62]), "+f"(d[63]),
          "+f"(d[64]), "+f"(d[65]), "+f"(d[66]), "+f"(d[67]), "+f"(d[68]), "+f"(d[69]), "+f"(d[70]), "+f"(d[71]),
          "+f"(d[72]), "+f"(d[73]), "+f"(d[74]), "+f"(d[75]), "+f"(d[76]), "+f"(d[77]), "+f"(d[78]), "+f"(d[79])
        : "r"(a), "r"(b), "r"(scale_d));
}
__device__ __forceinline__ void wgmma_reg64(float (&d)[80], uint32_t a0, uint32_t a1, uint32_t a2, uint32_t a3, uint32_t b, int scale_d) {
    asm volatile("{\n.reg .pred p;\n.reg .b64 db;\nsetp.ne.b32 p, %37, 0;\nmov.b64 db, {%36, 0x40000040};\n"
        "wgmma.mma_async.sync.aligned.m64n64k16.f32.bf16.bf16 "
        "{%0, %1, %2, %3, %4, %5, %6, %7, %8, %9, %10, %11, %12, %13, %14, %15, "
        "%16, %17, %18, %19, %20, %21, %22, %23, %24, %25, %26, %27, %28, %29, %30, %31}, "
        "{%32, %33, %34, %35}, db, p, 1, 1, 1;\n}\n"
        : "+f"(d[0]), "+f"(d[1]), "+f"(d[2]), "+f"(d[3]), "+f"(d[4]), "+f"(d[5]), "+f"(d[6]), "+f"(d[7]),
          "+f"(d[8]), "+f"(d[9]), "+f"(d[10]), "+f"(d[11]), "+f"(d[12]), "+f"(d[13]), "+f"(d[14]), "+f"(d[15]),
          "+f"(d[16]), "+f"(d[17]), "+f"(d[18]), "+f"(d[19]), "+f"(d[20]), "+f"(d[21]), "+f"(d[22]), "+f"(d[23]),
          "+f"(d[24]), "+f"(d[25]), "+f"(d[26]), "+f"(d[27]), "+f"(d[28]), "+f"(d[29]), "+f"(d[30]), "+f"(d[31])
        : "r"(a0), "r"(a1), "r"(a2), "r"(a3), "r"(b), "r"(scale_d));
}
__device__ __forceinline__ void wgmma_reg96(float (&d)[80], uint32_t a0, uint32_t a1, uint32_t a2, uint32_t a3, uint32_t b, int scale_d) {
    asm volatile("{\n.reg .pred p;\n.reg .b64 db;\nsetp.ne.b32 p, %53, 0;\nmov.b64 db, {%52, 0x40000040};\n"
        "wgmma.mma_async.sync.aligned.m64n96k16.f32.bf16.bf16 "
        "{%0, %1, %2, %3, %4, %5, %6, %7, %8, %9, %10, %11, %12, %13, %14, %15, "
        "%16, %17, %18, %19, %20, %21, %22, %23, %24, %25, %26, %27, %28, %29, %30, %31, "
        "%32, %33, %34, %35, %36, %37, %38, %39, %40, %41, %42, %43, %44, %45, %46, %47}, "
        "{%48, %49, %50, %51}, db, p, 1, 1, 1;\n}\n"
        : "+f"(d[32]), "+f"(d[33]), "+f"(d[34]), "+f"(d[35]), "+f"(d[36]), "+f"(d[37]), "+f"(d[38]), "+f"(d[39]),
          "+f"(d[40]), "+f"(d[41]), "+f"(d[42]), "+f"(d[43]), "+f"(d[44]), "+f"(d[45]), "+f"(d[46]), "+f"(d[47]),
          "+f"(d[48]), "+f"(d[49]), "+f"(d[50]), "+f"(d[51]), "+f"(d[52]), "+f"(d[53]), "+f"(d[54]), "+f"(d[55]),
          "+f"(d[56]), "+f"(d[57]), "+f"(d[58]), "+f"(d[59]), "+f"(d[60]), "+f"(d[61]), "+f"(d[62]), "+f"(d[63]),
          "+f"(d[64]), "+f"(d[65]), "+f"(d[66]), "+f"(d[67]), "+f"(d[68]), "+f"(d[69]), "+f"(d[70]), "+f"(d[71]),
          "+f"(d[72]), "+f"(d[73]), "+f"(d[74]), "+f"(d[75]), "+f"(d[76]), "+f"(d[77]), "+f"(d[78]), "+f"(d[79])
        : "r"(a0), "r"(a1), "r"(a2), "r"(a3), "r"(b), "r"(scale_d));
}
__device__ __forceinline__ void wgmma_reg(float (&d)[80], uint32_t a0, uint32_t a1, uint32_t a2, uint32_t a3, uint32_t b, int scale_d) {
    wgmma_reg64(d, a0, a1, a2, a3, b, scale_d);
    wgmma_reg96(d, a0, a1, a2, a3, b + 640, scale_d);
}
#define TSQ(i) do { } while (0)
#define TSR(i) do { } while (0)
#define MAP_TILE(b) (((b) & 1) | (((b) >> 1) & 2) | (((b) >> 5) << 2))
#define MAP_HG(b) (((((b) >> 2) & 6) ^ (((b) & 32) ? 2 : 4)) | ((((b) >> 1) ^ ((b) >> 2) ^ ((b) >> 3) ^ ((b) >> 5) ^ 1) & 1))
#define SKEW 4
#define PACE 500
#define PACE_W0 (-600)
#define PACE_A 250
#define PACE_B 450
#define RG_T0 1700
#define RG_DT 200
#define GU_T0 3600
#define GU_DT 500
#define RS_T0 9200
#define RS_DT 200
#define HALO_D 300
#define PF_UP 7000
#define PF_DT 450
#define O_D 250
#define O_DT 300
#define C1_D 0
#define C2_D 0
#define C5_D 0
#define C6_D 100
#define C7_D 100
#define GH_DT 300
#define GX_D 400
#define Y_AT 1
#define CAND_T 8100
#define DN_D 0
#define GATE_T 9000
#define GH_T0 6800
#define NRS 2
#define DN0(q) ((q) * 3 - ((q) == 3))
#define WO_D ((uint64_t)(C1_D / 16) << 8 | (uint64_t)(C2_D / 16) * 0x10101 << 16 | (uint64_t)(C5_D / 16) << 40 | (uint64_t)(C6_D / 16) << 48 | (uint64_t)(C7_D / 16) << 56)

__device__ __forceinline__ uint32_t keep(uint32_t v) { return __shfl_sync(0xffffffffu, v, threadIdx.x); }
__device__ __forceinline__ uint32_t ukeep(uint32_t v) { return __shfl_sync(0xffffffffu, v, 0); }
__device__ __forceinline__ void ldsm2(uint32_t* d, uint32_t a) {
    asm volatile("ldmatrix.sync.aligned.m8n8.x4.shared.b16 {%0,%1,%2,%3}, [%8];\nldmatrix.sync.aligned.m8n8.x4.shared.b16 {%4,%5,%6,%7}, [%9];"
                 : "=r"(d[0]), "=r"(d[1]), "=r"(d[2]), "=r"(d[3]), "=r"(d[4]), "=r"(d[5]), "=r"(d[6]), "=r"(d[7])
                 : "r"(a), "r"(a ^ 32) : "memory");
}
__device__ __forceinline__ void stsm(uint32_t a, uint32_t x, uint32_t y, uint32_t z, uint32_t w) {
    asm volatile("stmatrix.sync.aligned.m8n8.x4.shared.b16 [%0], {%1,%2,%3,%4};" ::"r"(a), "r"(x), "r"(y), "r"(z), "r"(w) : "memory");
}
__device__ __forceinline__ void row_sums(float& sa, float& sb, float a0, float a1, float b0, float b1) {
    asm volatile("{\n.reg .f32 x, y;\nmma.sync.aligned.m16n8k8.row.col.f32.tf32.tf32.f32 {%0,x,%1,y}, {%2,%3,%4,%5}, {%6,%6}, {%7,%7,%7,%7};\n}"
                 : "=f"(sa), "=f"(sb) : "r"(f2u(a0)), "r"(f2u(b0)), "r"(f2u(a1)), "r"(f2u(b1)), "r"(0x3F800000), "f"(0.f));
}
template <bool SWP, int SEG, int E>
__device__ __forceinline__ void pack_blocks(uint32_t (&d)[10], const float (&am)[96], const float (&ar)[24]) {
#pragma unroll
    for (int t = 0; t < 10; t++) {
        const float* p = (SWP ? t < 2 : t >= 8) ? ar + (SEG * 2 + (t & 1)) * 4 + E : am + (SEG * 8 + t - (SWP ? 2 : 0)) * 4 + E;
        d[t] = pack2v(p[0], p[1]);
    }
}
#define HALF(hg) ((hg) >> 2)
#define CB(hg) ((hg) & 3)
__device__ __forceinline__ int src_of(int i, int hg) {
    return i == 0 ? hg : (i - (i <= (hg | 4))) ^ (~hg & 4);
}

__device__ __forceinline__ uint32_t o_buf(int i) { return __byte_perm(0x5B000000u, 0x473D6F65u, i) << 10; }
__device__ constexpr uint32_t wo_buf(int i) { return SM_W + ((0x10546103u >> i * 4) & 7) * 30720; }

template <int N>
__device__ __forceinline__ void poll(uint4 (&a)[N], const uint4* p, int stride) {
    bool bad;
    do {
        bad = false;
#pragma unroll
        for (int s = 0; s < N; s++) a[s] = ld_relaxed16(p + s * stride);
#pragma unroll
        for (int s = 0; s < N; s++) bad |= a[s].w == SENT;
    } while (__any_sync(0xffffffffu, bad));
}
__device__ __forceinline__ void pace(unsigned t0, int t) {
    asm volatile("{\n.reg .pred p;\n.reg .s32 d;\nAGAIN:\nmov.u32 d, %%clock;\nsub.s32 d, d, %0;\nsetp.lt.s32 p, d, 0;\n"
                 "@p nanosleep.u32 20;\n@p bra AGAIN;\n}" ::"r"(t0 + t) : "memory");
}
__device__ __forceinline__ void l2_prefetch(const void* p) { asm volatile("prefetch.global.L2 [%0];" ::"l"(p) : "memory"); }

template <int ROW>
__device__ __forceinline__ void wgmma_vec(float (&d)[8], uint32_t a, uint32_t b, int scale_d) {
    asm volatile("{\n.reg .pred p;\n.reg .b64 da, db;\nsetp.ne.b32 p, %10, 0;\nmov.b64 da, {%8, 0x40000040};\nmov.b64 db, {%9, %11};\n"
                 "wgmma.mma_async.sync.aligned.m64n16k16.f32.bf16.bf16 {%0, %1, %2, %3, %4, %5, %6, %7}, da, db, p, 1, 1, 1, 0;\n}"
                 : "+f"(d[0]), "+f"(d[1]), "+f"(d[2]), "+f"(d[3]), "+f"(d[4]), "+f"(d[5]), "+f"(d[6]), "+f"(d[7])
                 : "r"(a), "r"(b), "r"(scale_d), "n"(ROW / 16));
}

__global__ void __launch_bounds__(512, 1) fused_kernel(const __grid_constant__ Params P) {
    extern __shared__ __align__(1024) uint8_t smem_raw[];
    const unsigned t_start = clock();
    const int tid = threadIdx.x, lane = tid & 31;
    const int warp = __shfl_sync(0xffffffffu, tid >> 5, 0);
    const int tile = MAP_TILE(blockIdx.x), hg = MAP_HG(blockIdx.x);
    const int cid = tile * 8 + hg;
    const int par = tile & 1, p0 = (tile >> 1) * 128;
    uint4* const sc = g_sc + cid * SC_SIZE;
    const int fid = ((blockIdx.x - 8) & 127) ^ (~blockIdx.x >> 1 & 2);
    const bool swp = (hg & 3) == 3;
    const int wcm = hg * 80 + (swp ? 16 : 0), wcr = hg * 80 + (swp ? 0 : 64);
    if (warp < 7 && elect_one()) {
#pragma unroll
        for (int i = 0; i < 4; i++) mbar_init(SM_BAR + warp * 32 + i * 8, warp < 4 ? 1 : warp < 6 ? 2 : 4);
        asm volatile("fence.mbarrier_init.release.cluster;" ::: "memory");
        if (warp == 0) {
            mbar_expect_tx(B_FULL, 15360 + 8192);
            tma_3d(SM_X + 8192, &P.x, B_FULL, 0, par, p0 + 64);
            tma_3d(SM_W, &P.w, B_FULL, wcm, 0, 0);
            tma_3d(SM_W + 12288, &P.wr, B_FULL, wcr, 0, 0);
            TS(40);
            mbar_expect_tx(B_XL0, 8192);
            tma_3d(SM_X, &P.x, B_XL0, 0, par, p0);
        }
    }
    __syncthreads();

    if (warp >= 12) {
        asm volatile("setmaxnreg.dec.sync.aligned.u32 32;");
        if (warp == 12) {
            if (elect_one()) {
#pragma unroll 1
                for (int s = 1; s < 20; s++) {
                    const uint32_t fb = B_FULL + (s & 7) * 8, dst = SM_W + (s & 7) * 15360;
                    mbar_wait(fb + (B_EMPTY - B_FULL), ~(s >> 3) & 1);
                    pace(t_start, max(PACE_A + s * PACE_B, PACE_W0 + s * PACE));
                    mbar_expect_tx(fb, (s & 1) ? 15360 : 15360 + 16384);
                    tma_3d(dst, &P.w, fb, wcm, s * 32, 0);
                    tma_3d(dst + 12288, &P.wr, fb, wcr, s * 32, 0);
                    TS2(20 + s);
                    if (s == 1) TS(41);
                }
                mbar_wait(B_RG2, 0);
                if (fid < NFFN) {
                    const int nd = 3 - (fid >> 1 & 1);
                    mbar_expect_tx(B_UP, 6144);
                    mbar_expect_tx(B_DN, nd * 8192);
                    mbar_wait(B_EMPTY + 4 * 8, 1);
                    TSQ(40);
                    tma_2d(SM_UP, &P.up2, B_UP, (fid >> 2) * 64, (fid & 3) * 160 + 112);
                    mbar_wait(B_EMPTY + 5 * 8, 1);
                    const unsigned t0 = clock();
#pragma unroll 1
                    for (int i = 0; i < nd; i++) {
                        pace(t0, i * DN_D);
                        tma_3d(SM_DN + i * 8192, &P.down, B_DN, 0, (fid >> 2) * 64, DN0(fid & 3) + i);
                    }
                    TSQ(41);
                }
                const int cb = CB(hg), ca = (cb * 5 + 1) >> 1, cr = cb * 160 + ((cb & 1) ? 0 : 128);
                unsigned t1 = 0;
#pragma unroll 1
                for (int j = 0; j < 8; j++) {
                    const int i = j ^ (j == 3 || j == 4 ? 7 : 0);
                    if (j != 3) mbar_wait(j < 3 ? B_EMPTY + ((2 * j + 7) & 7) * 8 : j == 5 ? B_HF : B_GUD + (j - 4) * 8, j == 0);
                    if (j != 3 && j != 4) t1 = clock();
                    pace(t1, (WO_D >> j * 8 & 255) * 16);
                    const uint32_t dst = wo_buf(i), gb = B_G2 + i * 8;
                    TSQ(20 + j);
                    mbar_expect_tx(gb, 25600);
                    tma_3d(dst, &P.woa, gb, 0, src_of(i, hg) * 80, ca);
                    tma_2d(dst + 20480, &P.wob, gb, cr, src_of(i, hg) * 80);
                }
            }
        } else if (warp == 14) {
            if (elect_one()) {
#pragma unroll 1
                for (int kb = 1; kb < 10; kb++) {
                    const uint32_t fb = B_FULL + (kb & 3) * 16, dst = SM_X + (kb & 3) * 16384;
                    mbar_wait(fb + (B_EMPTY - B_FULL + 8), ~(kb >> 2) & 1);
                    if (kb >= 4) mbar_wait(B_XE + (kb - 4 >> 1) * 8, 0);
                    pace(t_start, max(PACE_A - PACE_B / 2 + 2 * kb * PACE_B, PACE_W0 - 50 + (2 * kb + 1) * PACE));
                    tma_3d(dst, &P.x2, fb, kb * 64, par, p0);
                }
            }
            __syncwarp();
            mbar_wait(B_ALL, 0);
            bar_sync(12, 64);
            pace(clock(), HALO_D);
            uint4 hv[5];
            poll<5>(hv, sc + (SC_HALO - (tile < 2 ? 0 : 16 * SC_SIZE) + lane), 32);
#pragma unroll
            for (int s = 0; s < 5; s++) sts16(SM_HALO + s * 512 + lane * 16, hv[s].x, hv[s].y, hv[s].z, hv[s].w);
            bar_arrive(8, 64);
            TSM(25);
        } else if (warp == 15) {
            int it = smem_u32(smem_raw) == SB ? 0 : 1 << 20;
            while (!mbar_try(B_XE + 16, 0))
                if (++it > (1 << 20)) fault();
            TSR(44);
            const uint32_t key = lds4(SM_KEY + (lane & 15) * 4), epoch = lds4(SM_KEY + 20 * 4);
            uint32_t k1 = __reduce_max_sync(0xffffffffu, key);
            uint32_t k2 = __reduce_max_sync(0xffffffffu, key == k1 ? 0u : key);
            if (elect_one()) {
                st_relaxed16(g_cand + cid, k1, k2, epoch, epoch);
                red_inc(g_cnt, epoch);
                TSR(45);
                if (fid < NFFN) {
                    mbar_expect_tx(B_GU, 10240);
                    pace(t_start, GH_T0);
                    tma_2d(SM_G, &P.up, B_GU, (fid >> 2) * 64, (fid & 3) * 160 + 32);
                    pace(clock(), GH_DT);
                    tma_2d(SM_G + 4096, &P.up2, B_GU, (fid >> 2) * 64, (fid & 3) * 160 + 64);
                }
            }
            __syncwarp();
            pace(t_start, CAND_T);
            TSR(46);
            uint4 cd[4];
            do {
                TSR(47);
#pragma unroll
                for (int j = 0; j < 4; j++) cd[j] = ld_relaxed16(g_cand + lane + 32 * j);
                if (++it > (1 << 20)) fault();
            } while (!__all_sync(0xffffffffu, cd[0].z == epoch && cd[1].z == epoch && cd[2].z == epoch && cd[3].z == epoch));
            TSR(48);
            uint32_t l1 = 0, l2 = 0;
#pragma unroll
            for (int j = 0; j < 4; j++) {
                l2 = max(max(l2, cd[j].y), min(l1, cd[j].x));
                l1 = max(l1, cd[j].x);
            }
            k1 = __reduce_max_sync(0xffffffffu, l1);
            k2 = __reduce_max_sync(0xffffffffu, l1 == k1 ? l2 : l1);
            if (elect_one()) {
                bulk_load(SM_XS, P.xp + (~k1 & 2047) * 640 + (fid & 3) * 160, 320, B_XS);
                bulk_load(SM_XS + 320, P.xp + (~k2 & 2047) * 640 + (fid & 3) * 160, 320, B_XS);
                sts16(SM_KEY + 16 * 4, k1, k2, 0, 0);
                mbar_expect_tx(B_XS, 640);
                mbar_arrive(B_ALL);
                TSR(49);
            }
            __syncwarp();
            while (!mbar_try(B_DONE, 0) || !mbar_try(B_MOD, 0))
                if (++it > (1 << 20)) fault();
        } else {
#pragma unroll 1
            for (int i = 0; i < 10; i++) sts16(SM_SENT + i * 512 + lane * 16, SENT, SENT, SENT, SENT);
            fence_async_smem();
            __syncwarp();
            if (elect_one()) {
                mbar_expect_tx(B_RG, 2560);
                asm volatile("mbarrier.expect_tx.relaxed.cta.shared::cta.b64 [%0], 10240;" ::"r"(B_RG2) : "memory");
                asm volatile("mbarrier.expect_tx.relaxed.cta.shared::cta.b64 [%0], 24576;" ::"r"(B_GU) : "memory");
                bulk_load(SM_RED, P.w_r, 1280, B_RG);
                bulk_load(SM_RED + 1280, P.gate_w, 1280, B_RG);
#pragma unroll
                for (int i = 0; i < 24; i++) mbar_init(B_GUD + i * 8, i == 23 ? 8 : i == 0 || i == 22 ? 4 : i < 15 + NRS ? 1 : 2);
#pragma unroll 1
                for (int i = 0; i < 5; i++) {
                    pace(t_start, RG_T0 + i * RG_DT);
                    tma_3d(SM_G + i * 2048, &P.xg, B_RG2, 320 + i * 64, par, p0 + hg * 16);
                }
                bulk_store(sc + SC_HALO, SM_SENT, 5120);
                asm volatile("cp.async.bulk.commit_group;\ncp.async.bulk.wait_group 0;" ::: "memory");
                mbar_arrive(B_RG2);
                TS(43);
#pragma unroll 1
                for (int i = 0; i < (fid < NFFN ? 6 : 0); i++) {
                    pace(t_start, GU_T0 + i * GU_DT);
                    tma_2d(SM_F + i * 4096, i < 5 ? &P.gate : &P.up, B_GU, (fid >> 2) * 64, (fid & 3) * 160 + (i < 5 ? i * 32 : 0));
                }
            }
            __syncwarp();
            if (fid < NFFN) {
                const __nv_bfloat16* up = P.upp + ((fid & 3) * 160 + 112 + lane) * 1728 + (fid >> 2) * 64;
                pace(t_start, PF_UP - PF_DT);
                l2_prefetch(up);
                l2_prefetch(up + 16 * 1728);
            }
            const unsigned goal = (ld_relaxed4(g_cnt + 32) | (NCTA - 1)) + 1;
            if (elect_one()) {
#pragma unroll 1
                for (int i = 0; i < 4; i++) {
                    pace(t_start, RS_T0 + i * RS_DT);
                    bulk_store(sc + i * 320, SM_SENT, 5120);
                }
                asm volatile("cp.async.bulk.commit_group;\ncp.async.bulk.wait_group 0;" ::: "memory");
                red_inc(g_cnt + 32, goal);
                mbar_arrive(B_RS);
            }
            __syncwarp();
            TSQ(30);
            while (ld_relaxed4(g_cnt + 32) - goal > 0x80000000u) {}
            if (lane == 0) mbar_arrive(B_INIT);
            TS(45);
        }
    } else if (warp >= 8) {
        asm volatile("setmaxnreg.dec.sync.aligned.u32 96;");
        const int t = tid - 256;
        const unsigned epoch = ld_relaxed4(g_cnt) / NCTA + 1;
        float gv = 0.f;
        int grow = hg * 16 + (t >> 3);
        {
            const uint32_t sw = (t >> 4) * 128 + (((t ^ (t >> 4)) & 7) << 4), hi = (t >> 3) & 1;
            const uint32_t xs = keep(sw + SM_X + hi * 16384 + hg * 2048), xg = keep(sw + SM_G + hi * 2048), ws = SM_RED + (t & 15) * 16;
            uint4 a[5], b[5], w[5];
            float r0 = 0.f, r1 = 0.f;
            auto load = [&](int p, uint32_t xa) { a[p] = lds16(xa); b[p] = lds16(xa + 1024); w[p] = lds16(ws + p * 256); };
            auto dot = [&](int p) {
                const uint32_t as[4] = {a[p].x, a[p].y, a[p].z, a[p].w}, bs[4] = {b[p].x, b[p].y, b[p].z, b[p].w};
                const uint32_t vs[4] = {w[p].x, w[p].y, w[p].z, w[p].w};
#pragma unroll
                for (int e = 0; e < 4; e++) {
                    r0 = fmaf(bf_lo(as[e]), bf_lo(vs[e]), r0);
                    r1 = fmaf(bf_lo(bs[e]), bf_lo(vs[e]), r1);
                    r0 = fmaf(bf_hi(as[e]), bf_hi(vs[e]), r0);
                    r1 = fmaf(bf_hi(bs[e]), bf_hi(vs[e]), r1);
                }
                asm volatile("" : "+f"(r0), "+f"(r1), "+r"(a[p].x), "+r"(a[p].y), "+r"(a[p].z), "+r"(a[p].w),
                                  "+r"(b[p].x), "+r"(b[p].y), "+r"(b[p].z), "+r"(b[p].w));
            };
            auto release = [&](int p) {
                if (__ballot_sync(0xffffffffu, lane == 0 || (a[p].w ^ w[p].w) == b[p].w) && lane == 0) mbar_arrive(B_XE + p * 8);
            };
            auto total = [&]() {
                float r = (hi ? r1 : r0) + __shfl_xor_sync(0xffffffffu, hi ? r0 : r1, 8);
                r += __shfl_xor_sync(0xffffffffu, r, 4);
                r += __shfl_xor_sync(0xffffffffu, r, 2);
                return bf_round(r + __shfl_xor_sync(0xffffffffu, r, 1));
            };
            mbar_wait(B_RG, 0);
            mbar_wait(B_XL0, 0);
            mbar_wait(B_FULL, 0);
            mbar_wait(B_FULL + 16, 0);
            TSR(32);
            load(0, xs);
            release(0);
            dot(0);
            TSR(33);
            mbar_wait(B_RG2, 0);
            TSR(34);
            load(3, xg + 2048);
            load(4, xg + 6144);
            mbar_wait(B_FULL + 32, 0);
            mbar_wait(B_FULL + 48, 0);
            TSR(35);
            load(1, xs + 32768);
            dot(3);
            release(1);
            dot(4);
            TSR(36);
            mbar_wait(B_FULL, 1);
            TSR(37);
            load(2, hi ? xg - 2048 : xs);
            dot(1);
            dot(2);
            TSR(42);
            grow = hg * 16 + (t >> 4) + hi * 8;
            const uint32_t u = f2u(total());
            sts4(SM_KEY + (t >> 3) * 4, (((int)u < 0 ? ~u : u | 0x80000000u) & 0xFFFF0000u) | (2047 - (p0 + grow) * 2 - par));
            sts4(SM_KEY + 20 * 4, epoch);
            __syncwarp();
            if (lane == 0) mbar_arrive(B_XE + 16);
            TSR(43);
            r0 = r1 = 0.f;
#pragma unroll
            for (int p = 0; p < 5; p++) w[p] = lds16(ws + 1280 + p * 256);
#pragma unroll
            for (int p = 0; p < 5; p++) dot(p);
            gv = total();
        }
        if ((lane & 7) == 4) st_relaxed4(g_gate + tile * 128 + grow, f2u(bf_round(sigmoidf(gv))) | (epoch & 0xFFFFu));
        TSR(38);
        if (warp == 9) {
            pace(t_start, GATE_T);
            uint4 v;
            do {
                asm volatile("ld.relaxed.gpu.global.v4.u32 {%0, %1, %2, %3}, [%4];"
                             : "=r"(v.x), "=r"(v.y), "=r"(v.z), "=r"(v.w) : "l"(g_gate + tile * 128 + lane * 4) : "memory");
            } while (__any_sync(0xffffffffu, ((v.x ^ epoch) | (v.y ^ epoch) | (v.z ^ epoch) | (v.w ^ epoch)) & 0xFFFFu));
            sts16(SM_GATE + lane * 16, v.x & 0xFFFF0000u, v.y & 0xFFFF0000u, v.z & 0xFFFF0000u, v.w & 0xFFFF0000u);
            __syncwarp();
            if (lane == 0) mbar_arrive(B_GT);
        }
        mbar_wait(B_XS, 0);
        TS(warp == 8 ? 50 : 63);
        TSR(50);
        const int cq = lane & 3, q = fid & 3;
        if (fid < NFFN) {
            uint4* const sc = g_sc + fid * SC_SIZE;
            float ga[8], ua[8];
            mbar_wait(B_GU, 0);
            TS(warp == 8 ? 61 : 63);
            mbar_wait(B_UP, 0);
            TSR(52);
            bar_sync(13, 256);
            TSM(warp == 8 ? 53 : 63);
            wg_fence();
#pragma unroll
            for (int i = 0; i < 10; i++) {
                wgmma_vec<320>(ga, desc_lo(SM_F, 16) + i * 128, desc_lo(SM_XS, 16) + i * 2, i);
                wgmma_vec<320>(ua, desc_lo(i < 7 ? SM_F + 20480 : SM_UP - 14336, 16) + i * 128, desc_lo(SM_XS, 16) + i * 2, i);
            }
            wg_commit();
            wg_wait<0>();
            TSM(warp == 8 ? 54 : 63);
            if (cq == 0) {
                st_relaxed16(sc + SC_GU + (t >> 2), f2u(ga[0]), f2u(ga[2]), f2u(ga[4]), f2u(ga[6]));
                st_relaxed16(sc + SC_GU + 32 + (t >> 2), f2u(ua[0]), f2u(ua[2]), f2u(ua[4]), f2u(ua[6]));
            }
            if (lane == 0) mbar_arrive(B_GUD);
            uint4 pq[2];
            pace(clock(), GX_D);
            poll<2>(pq, sc + (cq - q) * SC_SIZE + SC_GU + (t >> 2), 32);
            TSR(55);
            const bool tk = cq & 2, c8 = cq & 1;
            float v[4];
#pragma unroll
            for (int m = 0; m < 2; m++) {
                v[2 * m] = u2f(tk ? pq[m].z : pq[m].x) + __shfl_xor_sync(0xffffffffu, u2f(tk ? pq[m].x : pq[m].z), 2);
                v[2 * m + 1] = u2f(tk ? pq[m].w : pq[m].y) + __shfl_xor_sync(0xffffffffu, u2f(tk ? pq[m].y : pq[m].w), 2);
                v[m] = bf_round((c8 ? v[2 * m + 1] : v[2 * m]) + __shfl_xor_sync(0xffffffffu, c8 ? v[2 * m] : v[2 * m + 1], 1));
            }
            const uint32_t h = pack2(bf_round(v[0] * sigmoidf(v[0])) * v[1], 0.f);
            asm volatile("st.shared.u16 [%0], %1;" ::"r"(SM_XS + (cq >> 1) * 128 + ((t >> 5) * 16 + (cq & 1) * 8 + (lane >> 2)) * 2),
                         "h"((uint16_t)h) : "memory");
            fence_async_smem();
            bar_sync(4, 128);
            TS(warp == 8 ? 57 : 63);
            mbar_wait(B_DN, 0);
            bar_sync(14, 384);
            TSR(56);
            float y[3][8];
#pragma unroll 1
            for (int i = 0; i < 4; i++) {
                wg_fence();
#pragma unroll
                for (int m = 0; m < 3; m++)
                    wgmma_vec<128>(y[m], desc_lo(SM_DN + m * 8192, 16) + i * 128, desc_lo(SM_XS, 16) + i * 2, i);
                wg_commit();
            }
            wg_wait<0>();
            if (cq == 0) {
#pragma unroll
                for (int m = 0; m < 6; m++)
                    asm volatile("st.relaxed.gpu.global.v2.f32 [%0], {%1, %2};"
                                 ::"l"(reinterpret_cast<float2*>(sc + SC_Y) + (m & 1) * 96 + (m >> 1) * 32 + (t >> 2)),
                                   "f"(y[m >> 1][(m & 1) * 4]), "f"(y[m >> 1][(m & 1) * 4 + 2]) : "memory");
            }
        } else if (lane == 0) {
            mbar_arrive(B_GUD);
        }
        if (lane == 0) mbar_arrive(B_DD);
        TSM(warp == 8 ? 51 : 63);
        const uint32_t k1 = lds4(SM_KEY + 16 * 4), k2 = lds4(SM_KEY + 17 * 4);
        const uint32_t mine = (tile >> 1) * 256 + HALF(hg) * 128 + par;
        const bool own1 = (~k1 & 0x781) == mine, own2 = (~k2 & 0x781) == mine;
        if ((own1 || own2) && NFFN) {
            const int rg = min(t / 40, 2), c40 = t % 40, un = CB(hg) * 40 + c40, src = un < 48 ? 0 : un < 96 ? 1 : un < 128 ? 2 : 3;
            const int col = min(t >> 3, 9) * 16 + (t & 1) * 8 + (t & 6);
            mbar_wait(B_OE + Y_AT * 8, 0);
            TS(warp == 8 ? 60 : 63);
#pragma unroll 1
            for (int j = !own1; j <= own2; j++) {
                const uint4* p = g_sc + (rg * 4 + src) * SC_SIZE + SC_Y + j * 48 + un - DN0(src) * 16;
                const uint32_t key = j ? k2 : k1;
                const uint32_t xv = *reinterpret_cast<const uint32_t*>(P.xp + (~key & 2047) * 640 + CB(hg) * 160 + col);
                float y[4];
                bool bad;
                do {
                    uint4 yp[9];
#pragma unroll
                    for (int i = 0; i < 9; i++) yp[i] = ld_relaxed16(p + i * 12 * SC_SIZE);
                    y[0] = y[1] = y[2] = y[3] = 0.f;
                    bad = false;
#pragma unroll
                    for (int i = 0; i < 9; i++) {
                        y[0] += u2f(yp[i].x); y[1] += u2f(yp[i].y); y[2] += u2f(yp[i].z); y[3] += u2f(yp[i].w);
                        bad |= max(max(yp[i].x, yp[i].y), max(yp[i].z, yp[i].w)) == SENT;
                    }
                } while (__any_sync(0xffffffffu, bad));
                TS(warp == 8 ? 62 : 63);
                sts16(SM_Y + j * 2048 + t * 16, f2u(y[0]), f2u(y[1]), f2u(y[2]), f2u(y[3]));
                bar_sync(4, 128);
                if (t < 80) {
                    const uint32_t ya = SM_Y + j * 2048 + (t >> 1) * 16 + (t & 1) * 4;
                    const float rs = bf_round(sigmoidf(u2f(((int)key < 0 ? key & 0x7FFFFFFFu : ~key) & 0xFFFF0000u)));
                    const float y0 = u2f(lds4(ya)) + u2f(lds4(ya + 640)) + u2f(lds4(ya + 1280));
                    const float y1 = u2f(lds4(ya + 8)) + u2f(lds4(ya + 648)) + u2f(lds4(ya + 1288));
                    sts4(SM_U + j * 320 + t * 4, hadd2(xv, pack2(bf_round(y0) * rs, bf_round(y1) * rs)));
                }
            }
            const int cc = col + (CB(hg) & 1 ? (col < 32 ? 128 : -32) : 0);
            mbar_wait(B_DONE, 0);
#pragma unroll 1
            for (int j = !own1; j <= own2; j++) {
                const uint32_t tk = ~(j ? k2 : k1) & 2047, rr = tk >> 1 & 15, stg = SM_OUT + (tk >> 5 & 3) * 5120;
                const float n = 1.f - u2f(lds4(SM_GATE + (tk & 254) * 2)), chk = u2f(lds4(stg + rr * 128 + (rr & 7) * 16));
                if (chk != chk) mbar_wait(B_OE + 24, 0);
                const uint32_t a = lds4(stg + (cc & 6) * 2 + (cc < 128 ? (cc >> 6) * 2048 + rr * 128 + (((cc >> 3 ^ rr) & 7) << 4)
                                                                       : 4096 + rr * 64 + (((cc >> 3 ^ rr >> 1) & 3) << 4)));
                if (t < 80)
                    *reinterpret_cast<uint32_t*>(P.op + tk * 640 + CB(hg) * 160 + col) = hfma2(pack2(n, n), lds4(SM_U + j * 320 + t * 4), a);
            }
        }
        if (t == 0) mbar_arrive(B_MOD);
        TS(warp == 8 ? 52 : 63);
    } else {
        asm volatile("setmaxnreg.inc.sync.aligned.u32 192;");
        const int wg = warp >> 2;
        const bool leader = (tid & 127) == 0;
        bool rel = false;
        uint32_t nb[40];
        const int odd = CB(hg) & 1, kba = ukeep(wg == HALF(hg) ? (CB(hg) * 5 + 1) >> 1 : 16), kbr = ukeep(kba + 2 - odd * 3);
        const int kbs = wg ? -1 : (20 - SKEW) / 2;
        const uint32_t xrow = keep(SM_X + (warp * 16 + (lane & 15)) * 128 + (((lane >> 4) ^ (lane & 7)) << 4));
        const int w4 = warp & 3, r = lane >> 2, cq = lane & 3;
        float am[96], ar[24];
        TSM(warp == 0 ? 3 : 63);
        if (wg == 0) mbar_wait(B_XL0, 0);
#pragma unroll 1
        for (int kb = 0; kb < 10; kb++) {
            const uint32_t fb = B_FULL + (kb & 3) * 16, wo = (kb & 3) * 1920, ph = (kb >> 2) & 1;
            const uint32_t xo = desc_lo(SM_X, 16) + wg * 512 + (kb & 3) * 1024;
#pragma unroll
            for (int h = 0; h < 2; h++) {
                mbar_wait(fb + h * 8, ph);
                if (kb == 0 && h == 0) TS(warp == 0 ? 0 : warp == 4 ? 16 : 63);
                TS2(warp == 4 ? kb * 2 + h : 63);
                if (h == 1) {
                    const uint32_t xa = xrow + (kb & 3) * 16384;
                    if (kb == kba) { ldsm2(nb, xa); ldsm2(nb + 8, xa ^ 64); }
                    if (kb == kba + 1) { ldsm2(nb + 16, xa); ldsm2(nb + 24, xa ^ 64); }
                    if (kb == kbr) ldsm2(nb + 32, xa ^ (odd * 64));
                }
                wg_wait<1>();
                if (rel) mbar_arrive(B_EMPTY + ((kb * 16 - 16) & 48) + h * 8);
                if (h == (SKEW & 1) && kb == kbs) bar_sync(5, 256);
                wg_fence();
                wgmma_main(am, xo + h * 4, desc_lo(SM_W + h * 15360, 4096) + wo, h || kb);
                wgmma_rem(ar, xo + h * 4, desc_lo(SM_W + h * 15360 + 12288, 1024) + wo, h || kb);
                wgmma_main(am, xo + h * 4 + 2, desc_lo(SM_W + h * 15360 + 2048, 4096) + wo, 1);
                wgmma_rem(ar, xo + h * 4 + 2, desc_lo(SM_W + h * 15360 + 12288 + 512, 1024) + wo, 1);
                wg_commit();
            }
            rel = leader;
        }
        if (wg == 1) bar_arrive(5, 256);
        if (wg == 0) bar_arrive(13, 256);
        mbar_wait(B_EMPTY + 7 * 8 - wg * 16, 1);
        wg_wait<0>();
        if (rel) mbar_arrive(B_EMPTY + 3 * 8);
        TSM(warp == 0 ? 2 : warp == 4 ? 18 : 63);

        uint32_t kl[10], kh[10], vl[10], vh[10], ql[10], qh[10], kp[10], vp[10];
        if (swp) {
            pack_blocks<true, 1, 2>(kh, am, ar);
            pack_blocks<true, 2, 2>(vh, am, ar);
        } else {
            pack_blocks<false, 1, 2>(kh, am, ar);
            pack_blocks<false, 2, 2>(vh, am, ar);
        }
        const uint32_t pbuf = (wg ? SM_HALO1 : SM_HALO) + w4 * 2560 + lane * 16;
        const uint32_t hbuf = warp == 3 ? SM_HALO1 + lane * 16 : pbuf + 2560;
        {
            const uint32_t ex[20] = {kh[0], kh[1], kh[3], kh[4], kh[5], kh[6], kh[8], kh[9], kh[2], kh[7],
                                     vh[0], vh[1], vh[2], vh[3], vh[4], vh[5], vh[6], vh[7], vh[8], vh[9]};
            if (warp == 7) {
                uint4* const hp = sc + SC_HALO + lane;
#pragma unroll
                for (int s = 0; s < 5; s++) st_relaxed16(hp + s * 32, ex[4 * s], ex[4 * s + 1], ex[4 * s + 2], ex[4 * s + 3]);
                bar_arrive(12, 64);
            } else {
#pragma unroll
                for (int s = 0; s < 5; s++) sts16(hbuf + s * 512, ex[4 * s], ex[4 * s + 1], ex[4 * s + 2], ex[4 * s + 3]);
            }
        }
        if (warp == 3) bar_arrive(11, 64);
        if (swp) {
            pack_blocks<true, 2, 0>(vl, am, ar);
            pack_blocks<true, 0, 0>(ql, am, ar);
            pack_blocks<true, 0, 2>(qh, am, ar);
            pack_blocks<true, 1, 0>(kl, am, ar);
        } else {
            pack_blocks<false, 2, 0>(vl, am, ar);
            pack_blocks<false, 0, 0>(ql, am, ar);
            pack_blocks<false, 0, 2>(qh, am, ar);
            pack_blocks<false, 1, 0>(kl, am, ar);
        }
#pragma unroll
        for (int t = 0; t < 10; t++) { vl[t] = movm(vl[t]); vh[t] = movm(vh[t]); }
        mbar_wait(B_RS, 0);
        mbar_wait(B_GT, 0);
        const float g0 = u2f(lds4(SM_GATE + warp * 64 + (lane & 28))), g1 = u2f(lds4(SM_GATE + 32 + warp * 64 + (lane & 28)));

        const bool no_prev = warp == 0 && tile < 2, low = cq < 2;
        const bool le0 = 2 * cq <= r, le1 = 2 * cq + 1 <= r;
        const uint32_t mle = (le0 ? 0xFFFFu : 0u) | (le1 ? 0xFFFF0000u : 0u);
        const float scl = 0.22360679774997896f * 1.4426950408889634f;
        uint32_t pl[4], ph[4], ol[10], oh[10], cl = 0;
        {
            float sl[4][4], sh[4][4], sp[4][4];
            bar_sync(6 + wg, 128);
            if (w4 == 0) bar_sync(8 + wg * 3, 64);
            {
                const uint4 a = lds16(pbuf), b = lds16(pbuf + 512), c = lds16(pbuf + 1024), d = lds16(pbuf + 1536), e = lds16(pbuf + 2048);
                kp[0] = a.x; kp[1] = a.y; kp[3] = a.z; kp[4] = a.w; kp[5] = b.x; kp[6] = b.y; kp[8] = b.z; kp[9] = b.w;
                kp[2] = c.x; kp[7] = c.y; vp[0] = c.z; vp[1] = c.w; vp[2] = d.x; vp[3] = d.y; vp[4] = d.z; vp[5] = d.w;
                vp[6] = e.x; vp[7] = e.y; vp[8] = e.z; vp[9] = e.w;
            }
#pragma unroll
            for (int h = 0; h < 4; h++) {
                const int ta = (h >> 1) * 5 + (h & 1) * 3, tc = (h >> 1) * 5 + 2;
                const uint32_t ml = low != (h & 1) ? ql[tc] : 0u, mh = low != (h & 1) ? qh[tc] : 0u;
#pragma unroll
                for (int e = 0; e < 4; e++) sl[h][e] = sh[h][e] = sp[h][e] = 0.f;
                mma16(sl[h], ql[ta], qh[ta], ql[ta + 1], qh[ta + 1], kl[ta], kl[ta + 1]);
                mma16(sh[h], ql[ta], qh[ta], ql[ta + 1], qh[ta + 1], kh[ta], kh[ta + 1]);
                mma8(sl[h], ml, mh, kl[tc]);
                mma8(sh[h], ml, mh, kh[tc]);
            }
#pragma unroll
            for (int h = 0; h < 4; h++) {
                const int ta = (h >> 1) * 5 + (h & 1) * 3, tc = (h >> 1) * 5 + 2;
                mma16(sp[h], ql[ta], qh[ta], ql[ta + 1], qh[ta + 1], kp[ta], kp[ta + 1]);
                mma8(sp[h], low != (h & 1) ? ql[tc] : 0u, low != (h & 1) ? qh[tc] : 0u, kp[tc]);
            }
#pragma unroll
            for (int t = 0; t < 10; t++) vp[t] = movm(vp[t]);
#pragma unroll
            for (int h = 0; h < 4; h++) {
                if (no_prev) sp[h][0] = sp[h][1] = -1e9f / 0.22360679774997896f;
                float a0 = le0 ? sl[h][0] : sp[h][0], a1 = le1 ? sl[h][1] : sp[h][1];
                float b0 = le0 ? sh[h][2] : sl[h][2], b1 = le1 ? sh[h][3] : sl[h][3];
                float ma = fmaxf(a0, a1), mb = fmaxf(b0, b1);
                ma = fmaxf(ma, __shfl_xor_sync(0xffffffffu, ma, 1));
                mb = fmaxf(mb, __shfl_xor_sync(0xffffffffu, mb, 1));
                ma = fmaxf(ma, __shfl_xor_sync(0xffffffffu, ma, 2));
                mb = fmaxf(mb, __shfl_xor_sync(0xffffffffu, mb, 2));
                ma *= -scl;
                mb *= -scl;
                a0 = ex2(fmaf(a0, scl, ma)), a1 = ex2(fmaf(a1, scl, ma));
                b0 = ex2(fmaf(b0, scl, mb)), b1 = ex2(fmaf(b1, scl, mb));
                row_sums(ma, mb, a0, a1, b0, b1);
                ma = rcp(ma) * g0;
                mb = rcp(mb) * g1;
                pl[h] = pack2(a0 * ma, a1 * ma);
                ph[h] = pack2(b0 * mb, b1 * mb);
            }
            uint32_t* const po = reinterpret_cast<uint32_t*>(sc + SC_O + warp * 160) + lane;
#pragma unroll
            for (int hp = 0; hp < 2; hp++) {
                float o[6][4];
#pragma unroll
                for (int h = 0; h < 2; h++) {
                    const int ta = hp * 5 + h * 3, tc = hp * 5 + 2;
                    const uint32_t a0 = pl[hp * 2 + h] & mle, a1 = ph[hp * 2 + h] & ~mle, a3 = ph[hp * 2 + h] & mle, ap = pl[hp * 2 + h] & ~mle;
#pragma unroll
                    for (int i = 0; i < 3; i++) o[h * 3 + i][0] = o[h * 3 + i][1] = o[h * 3 + i][2] = o[h * 3 + i][3] = 0.f;
#pragma unroll
                    for (int i = 0; i < 3; i++) mma8(o[h * 3 + i], a0, a1, vl[i < 2 ? ta + i : tc]);
#pragma unroll
                    for (int i = 0; i < 3; i++) mma16(o[h * 3 + i], ap, 0u, 0u, a3, vp[i < 2 ? ta + i : tc], vh[i < 2 ? ta + i : tc]);
                }
#pragma unroll
                for (int i = 0; i < 2; i++) {
                    ol[hp * 5 + i] = pack2(o[i][0], o[i][1]);
                    oh[hp * 5 + i] = pack2(o[i][2], o[i][3]);
                    ol[hp * 5 + 3 + i] = pack2(o[3 + i][0], o[3 + i][1]);
                    oh[hp * 5 + 3 + i] = pack2(o[3 + i][2], o[3 + i][3]);
                }
                ol[hp * 5 + 2] = pack2(low ? o[2][0] : o[5][0], low ? o[2][1] : o[5][1]);
                oh[hp * 5 + 2] = pack2(low ? o[2][2] : o[5][2], low ? o[2][3] : o[5][3]);
#pragma unroll
                for (int t = hp * 5; t < hp * 5 + 5; t++) {
                    st_relaxed4(po + t * 32, ol[t]);
                    st_relaxed4(po + t * 32 + 320, oh[t]);
                    if (t == 5) {
                        if (wg != HALF(hg)) bar_arrive(2, 256);
                        bar_arrive(14, 384);
                        if (lane == 0) mbar_arrive(B_HF);
                    }
                }
                if (!hp) cl = clock();
            }
        }
        TSM(warp == 0 ? 5 : warp == 4 ? 21 : warp == 5 ? 30 : warp == 1 ? 31 : warp == 2 ? 32 : warp == 3 ? 33 : warp == 6 ? 34 : 24);
        const uint4* ow = sc + (SC_O + HALF(hg) * 640 - hg * SC_SIZE);
        auto stage = [&]() {
            mbar_wait(B_INIT, 0);
            mbar_wait(B_OE, 0);
            const unsigned t0 = clock();
            uint32_t ph = 0;
#pragma unroll 1
            for (int i = w4 + 1 + NRS; i < 8; i += 4) {
                const uint4* src = ow + src_of(i, hg) * SC_SIZE;
                const uint32_t buf = o_buf(i), chk = buf + lane * 132;
                if (i >= 6) mbar_wait(B_DD, 0);
                pace(t0, (i - 3) * O_DT + O_D);
                uint32_t c;
                do {
                    if (elect_one()) {
                        mbar_expect_tx(B_OT + w4 * 8, 10240);
                        bulk_load(buf, src, 10240, B_OT + w4 * 8);
                    }
                    mbar_wait(B_OT + w4 * 8, ph);
                    if (i == 1 + NRS && !ph) TS(wg ? 19 : 20);
                    ph ^= 1;
                    c = max(max(lds4(chk), lds4(chk + 4096)), lds4(chk + 6144));
                } while (__any_sync(0xffffffffu, c == SENT));
                if (lane == 0) mbar_arrive(B_G2 + i * 8);
                TSM(32 + i);
            }
        };
        const bool idle = wg != HALF(hg);

        float oc[80];
        uint32_t routed = ~0u, n0, n1, stg, m128 = SM_SENT + lane * 16, m64 = m128, l128 = m128, l64 = m128, oa128, oa64;
        int orow;
        char *o128, *o64;
        bool nan;
        uint32_t c3 = 0;
        if (!idle || w4 == 3) {
        if (!idle) {
        uint32_t af[2][20];
        const uint32_t* const ap = reinterpret_cast<const uint32_t*>(ow + (~hg & 4) * SC_SIZE + w4 * 160) + lane;
        auto fetch = [&](int i) {
#pragma unroll
            for (int t = 0; t < 20; t++) af[i & 1][(t >> 1) + (t & 1) * 10] = ld_relaxed4(ap + i * SC_SIZE * 4 + ((t >> 1) + (t & 1) * 10) * 32);
        };
        auto missing = [&](int i, uint32_t c) {
            uint32_t m[3] = {af[i][0], af[i][1], ((uint32_t)clock() | c) >> 1};
#pragma unroll
            for (int t = 2; t < 20; t++) m[t / 2 % 3] = max(m[t / 2 % 3], af[i][t]);
            return __any_sync(0xffffffffu, max(max(m[0], m[1]), m[2]) == SENT);
        };
        auto addresses = [&](uint4 kv, uint32_t c2) {
            const uint32_t ln = lane + kv.z;
            orow = p0 + wg * 64 + w4 * 16;
            const uint32_t otok = orow * 2 + par, d1 = (~kv.x & 2047) - otok, d2 = (~kv.y & 2047) - otok;
            routed = (shl(~d1 & 1, d1 >> 1) | shl(~d2 & 1, d2 >> 1) | c2 << 16) & 0x7FFFFFFFu;
            n0 = routed >> r & 1 ? 0 : pack2(1.f - g0, 1.f - g0), n1 = routed >> r & 256 ? 0 : pack2(1.f - g1, 1.f - g1);
            stg = SM_OUT + w4 * 5120;
            m128 = stg + (ln & 15) * 128 + (((ln >> 4) ^ (ln & 7)) << 4);
            m64 = stg + 4096 + (ln & 15) * 64 + (((ln >> 4) ^ ((ln >> 1) & 3)) << 4);
            l128 = stg + (ln ^ (ln >> 3)) * 16;
            l64 = l128 + 4096;
            oa128 = otok * 1280 + kba * 128 + (ln >> 3) * (2560 - 128) + ln * 16;
            oa64 = otok * 1280 + kbr * 128 + odd * 64 + (ln >> 2) * (2560 - 64) + ln * 16;
            asm volatile("" : "+r"(n0), "+r"(n1), "+r"(routed), "+r"(m128), "+r"(m64), "+r"(l128), "+r"(oa128), "+r"(oa64));
            l64 = l128 + 4096;
        };
        auto step = [&](int i, int s) {
            wgmma_reg(oc, af[i][2 * s], af[i][10 + 2 * s], af[i][2 * s + 1], af[i][11 + 2 * s], desc_lo(wo_buf(i + 1), 10240) + s * 128, 1);
        };
        bar_sync(2, 256);
        mbar_wait(B_G2, 0);
        TSM(w4 == 0 ? 6 : 63);
        wg_fence();
#pragma unroll
        for (int s = 0; s < 5; s++)
            wgmma_reg(oc, ol[2 * s], oh[2 * s], ol[2 * s + 1], oh[2 * s + 1], desc_lo(wo_buf(0), 10240) + s * 128, s);
        wg_commit();
        mbar_wait(B_XS, 0);
        mbar_wait(B_INIT, 0);
        TSM(40 + w4);
        int nit = 0;
        const uint4 kv = lds16(SM_KEY + 64);
        fetch(0);
        uint32_t c1 = clock() | cl;
        wg_wait<0>();
        if (leader) mbar_arrive(B_OE);
        fetch(1);
        addresses(kv, clock());
        nit++;
        if (__builtin_expect(missing(0, c1), 0)) do {
            fetch(0);
            c1 = clock();
            fetch(1);
            nit++;
        } while (missing(0, c1));
        TSM(44 + w4);
        mbar_wait(B_G2 + 8, 0);
        TSM(w4 == 0 ? 7 : 63);
        wg_fence();
#pragma unroll
        for (int s = 0; s < 4; s++) step(0, s);
        const bool again = missing(1, 0);
        c1 = clock();
        step(0, 4);
        wg_commit();
        if (__builtin_expect(again, 0)) do fetch(1); while (missing(1, 0));
        TSM(56 + w4);
        mbar_wait(B_G2 + 16, 0);
        TSM(w4 == 0 ? 11 : 63);
        wg_fence();
#pragma unroll
        for (int s = 0; s < 5; s++) step(1, s);
        wg_commit();
        c3 = c1;
        wg_wait<1>();
        if (leader) mbar_arrive(B_OE + 8);
#pragma unroll 1
        for (int i = 3; i < 8; i++) {
            const uint32_t ao = desc_lo(0, 128) + (o_buf(i) >> 4), wo = desc_lo(0, 10240) + (wo_buf(i) >> 4);
            mbar_wait(B_G2 + i * 8, 0);
            TSM(w4 == 0 ? (i < 7 ? 9 + i : 17) : 63);
            wg_fence();
#pragma unroll
            for (int s = 0; s < 5; s++) wgmma_out64(oc, ao + s * 16, wo + s * 128, 1);
            wg_commit();
#pragma unroll
            for (int s = 0; s < 5; s++) wgmma_out96(oc, ao + s * 16, wo + 640 + s * 128, 1);
            wg_commit();
            if (i == 3) {
                wg_wait<2>();
                if (leader) mbar_arrive(B_OE + 16);
            }
        }
        o128 = reinterpret_cast<char*>(P.op) + oa128;
        o64 = reinterpret_cast<char*>(P.op) + oa64;
        TS(w4 == 0 ? 8 : 63);

        wg_wait<1>();
        TSM(w4 == 0 ? 9 : 63);
        }
        const bool rt0 = routed >> r & 1, rt1 = routed >> r & 256;
#pragma unroll
        for (int pi = 0; pi < 3; pi++) {
            const int part = pi < 2 ? 1 - pi : pi;
            if (pi == 1) {
                c3 |= clock();
                wg_wait<0>();
            }
            const int s0 = part ? part * 4 - 4 : 8, ns = part ? 4 : 2;
#pragma unroll
            for (int i = 0; i < 4; i++) {
                if (i >= ns) break;
                const int s = s0 + i;
                const uint32_t y0 = hfma2(n0, nb[s * 4], pack2(oc[s * 8 + 0], oc[s * 8 + 1]));
                const uint32_t y1 = hfma2(n1, nb[s * 4 + 1], pack2(oc[s * 8 + 2], oc[s * 8 + 3]));
                const uint32_t y2 = hfma2(n0, nb[s * 4 + 2], pack2(oc[s * 8 + 4], oc[s * 8 + 5]));
                const uint32_t y3 = hfma2(n1, nb[s * 4 + 3], pack2(oc[s * 8 + 6], oc[s * 8 + 7]));
                if (s == 0) nan = u2f(y0) != u2f(y0) || u2f(y1) != u2f(y1);
                stsm(((s < 8 ? m128 : m64) ^ ((s & 3) * 32)) + (s & 4) * 512, y0, y1, y2, y3);
            }
            __syncwarp();
            if (pi == 2 && lane == 0 && (int)routed >= 0) mbar_arrive(B_DONE);
            uint4 v[4];
#pragma unroll
            for (int i = 0; i < 4; i++)
                if (i < ns) v[i] = lds16(!part ? l64 + i * 512 : (l128 ^ ((i & 1) * 64)) + i * 512 + s0 * 512);
#pragma unroll
            for (int i = 0; i < 4; i++)
                if (i < ns && !(part ? routed >> (lane >> 3) & 1 << 4 * i : i ? rt1 : rt0))
                    *reinterpret_cast<uint4*>(!part ? o64 + i * 8 * 2560 : o128 + i * 4 * 2560 + s0 * 32) = v[i];
            if (pi == 0) TS(w4 == 0 ? 1 : 63);
        }
        TSM(w4 == 0 ? 10 : idle ? 62 : 63);
        }
        if (idle) {
            stage();
            return;
        }
        const bool rt0 = routed >> r & 1, rt1 = routed >> r & 256;
        uint32_t redo;
        asm volatile("{\n.reg .pred p, q;\nsetp.eq.u32 p, %1, 0xFFFFFFFF;\nbar.cta.red.or.pred q, 10, 128, p;\nselp.u32 %0, 1, 0, q;\n}"
                     : "=r"(redo) : "r"(nan ? SENT : c3 >> 1) : "memory");
        if (redo) {
            const int cb = CB(hg);
#pragma unroll 1
            for (int i = 0; i < 8; i++) {
                if (leader) {
                    mbar_expect_tx(B_RE, 25600);
                    tma_3d(SM_W, &P.woa, B_RE, 0, i * 80, (cb * 5 + 1) >> 1);
                    tma_2d(SM_W + 20480, &P.wob, B_RE, cb * 160 + ((cb & 1) ? 0 : 128), i * 80);
                }
#pragma unroll 1
                for (int s = 0; s < 20; s++) {
                    const int w = w4 * 640 + s * 32 + lane;
                    uint32_t v, it = 0;
                    do {
                        v = ld_relaxed4(reinterpret_cast<const uint32_t*>(ow + i * SC_SIZE) + w);
                        if (++it > (1u << 22)) fault();
                    } while ((v >> 16) == 0xFFFFu || (v & 0xFFFFu) == 0xFFFFu);
                    sts4(SM_X + w * 4, v);
                }
                fence_async_smem();
                __syncwarp();
                bar_sync(10, 128);
                mbar_wait(B_RE, i & 1);
                wg_fence();
#pragma unroll
                for (int s = 0; s < 5; s++) {
                    wgmma_out64(oc, desc_lo(SM_X, 128) + s * 16, desc_lo(SM_W, 10240) + s * 128, s || i);
                    wgmma_out96(oc, desc_lo(SM_X, 128) + s * 16, desc_lo(SM_W, 10240) + 640 + s * 128, s || i);
                }
                wg_commit();
                wg_wait<0>();
                bar_sync(10, 128);
            }
#pragma unroll
            for (int t = 0; t < 40; t++) {
                const int col = (t < 32 ? kba * 64 + (t >> 1) * 8 : kbr * 64 + odd * 32 + ((t - 32) >> 1) * 8) + cq * 2;
                const uint32_t y = hfma2((t & 1) ? n1 : n0, nb[t], pack2(oc[2 * t], oc[2 * t + 1]));
                sts4(stg + cq * 4 + (t < 32 ? (t >> 4) * 2048 + (r + (t & 1) * 8) * 128 + ((((t >> 1) & 7) ^ r) << 4)
                                            : 4096 + (r + (t & 1) * 8) * 64 + ((((t - 32) >> 1) ^ (r >> 1)) << 4)), y);
                if (!((t & 1) ? rt1 : rt0)) *reinterpret_cast<uint32_t*>(P.op + ((orow + r + (t & 1) * 8) * 2 + par) * 640 + col) = y;
            }
            bar_sync(10, 128);
            if (leader) mbar_arrive(B_OE + 24);
        }
    }
}

typedef CUresult (*EncodeFn)(CUtensorMap*, CUtensorMapDataType, cuuint32_t, void*, const cuuint64_t*, const cuuint64_t*,
                             const cuuint32_t*, const cuuint32_t*, CUtensorMapInterleave, CUtensorMapSwizzle,
                             CUtensorMapL2promotion, CUtensorMapFloatOOBfill);

void encode(EncodeFn fn, CUtensorMap* m, const void* ptr, int rank, const cuuint64_t* dims, const cuuint64_t* strides,
            const cuuint32_t* box, CUtensorMapSwizzle swz) {
    const cuuint32_t es[4] = {1, 1, 1, 1};
    fn(m, CU_TENSOR_MAP_DATA_TYPE_BFLOAT16, rank, const_cast<void*>(ptr), dims, strides, box, es,
       CU_TENSOR_MAP_INTERLEAVE_NONE, swz, CU_TENSOR_MAP_L2_PROMOTION_L2_128B, CU_TENSOR_MAP_FLOAT_OOB_FILL_NONE);
}

}

extern "C" void kernel_launch(void* const* d_in, const int* in_sizes, int n_in, void* d_out, int out_size) {
    (void)in_sizes; (void)n_in; (void)out_size;
    Params P;
    P.xp = (const __nv_bfloat16*)d_in[0];
    P.upp = (const __nv_bfloat16*)d_in[6];
    P.op = (__nv_bfloat16*)d_out;
    P.w_r = (const __nv_bfloat16*)d_in[4];
    P.gate_w = (const __nv_bfloat16*)d_in[8];

    void* fp = nullptr;
    cudaDriverEntryPointQueryResult st;
    cudaGetDriverEntryPoint("cuTensorMapEncodeTiled", &fp, cudaEnableDefault, &st);
    EncodeFn fn = (EncodeFn)fp;
    const cuuint64_t xd[3] = {640, 2, 1024}, xs[2] = {1280, 2560};
    const cuuint32_t bx[3] = {64, 1, 64}, bx2[3] = {64, 1, 128};
    encode(fn, &P.x2, d_in[0], 3, xd, xs, bx2, CU_TENSOR_MAP_SWIZZLE_128B);
    encode(fn, &P.x, d_in[0], 3, xd, xs, bx, CU_TENSOR_MAP_SWIZZLE_128B);
    const cuuint64_t wd[3] = {640, 640, 3}, ws[2] = {3840, 1280};
    const cuuint32_t bw[3] = {64, 32, 3}, bwr[3] = {16, 32, 3};
    encode(fn, &P.w, d_in[1], 3, wd, ws, bw, CU_TENSOR_MAP_SWIZZLE_128B);
    encode(fn, &P.wr, d_in[1], 3, wd, ws, bwr, CU_TENSOR_MAP_SWIZZLE_32B);
    const cuuint64_t ad[3] = {64, 640, 10}, as[2] = {1280, 128}, bd[2] = {640, 640};
    const cuuint32_t ba[3] = {64, 80, 2}, bb[2] = {32, 80};
    encode(fn, &P.woa, d_in[2], 3, ad, as, ba, CU_TENSOR_MAP_SWIZZLE_128B);
    encode(fn, &P.wob, d_in[2], 2, bd, as, bb, CU_TENSOR_MAP_SWIZZLE_128B);
    const cuuint64_t gd[2] = {1728, 640}, gs[1] = {3456}, dd[3] = {64, 1728, 10};
    const cuuint32_t bg[2] = {64, 32}, bu[2] = {64, 48}, bdn[3] = {64, 64, 1}, bxg[3] = {64, 1, 16};
    encode(fn, &P.xg, d_in[0], 3, xd, xs, bxg, CU_TENSOR_MAP_SWIZZLE_128B);
    encode(fn, &P.gate, d_in[5], 2, gd, gs, bg, CU_TENSOR_MAP_SWIZZLE_128B);
    encode(fn, &P.up, d_in[6], 2, gd, gs, bg, CU_TENSOR_MAP_SWIZZLE_128B);
    encode(fn, &P.up2, d_in[6], 2, gd, gs, bu, CU_TENSOR_MAP_SWIZZLE_128B);
    encode(fn, &P.down, d_in[7], 3, dd, as, bdn, CU_TENSOR_MAP_SWIZZLE_128B);

    cudaFuncSetAttribute(fused_kernel, cudaFuncAttributeMaxDynamicSharedMemorySize, SM_TOTAL);
    fused_kernel<<<NCTA, 512, SM_TOTAL, cudaStreamPerThread>>>(P);
}
```

```cpp
#include <cuda_runtime.h>
#include <cuda_bf16.h>
#include <cuda.h>
#include <stdint.h>

namespace {

constexpr int NCTA = 128;
constexpr int NFFN = 108;
constexpr uint32_t SENT = 0xFFFFFFFFu;

constexpr uint32_t SB = 1024;
constexpr uint32_t SM_W = SB;
constexpr uint32_t SM_X = SB + 122880;
constexpr uint32_t SM_F = SB + 188416;
constexpr uint32_t SM_G = SB + 212992;
constexpr uint32_t SM_BAR = SB + 223232;
constexpr uint32_t SM_PROF = SB + 223744;
constexpr uint32_t SM_KEY = SB + 224000;
constexpr uint32_t SM_RED = SB + 224128;
constexpr uint32_t SM_XS = SB + 226688;
constexpr uint32_t SM_SENT = SB + 227328;
constexpr uint32_t SM_U = SM_RED + 1920;
constexpr uint32_t SM_GATE = SM_RED;
constexpr uint32_t SM_TOTAL = 232448;
constexpr uint32_t SM_HALO1 = SM_X + 30720;
constexpr uint32_t SM_HALO = SM_HALO1 + 12800;
constexpr uint32_t SM_UP = SM_W + 61440;
constexpr uint32_t SM_DN = SM_UP + 6144;
constexpr uint32_t SM_Y = SM_F + 26624;
constexpr uint32_t SM_OUT = SM_W + 92160;

constexpr uint32_t B_XL0 = SM_BAR, B_FULL = SM_BAR + 8, B_GT = SM_BAR + 72, B_RG = SM_BAR + 80, B_RG2 = SM_BAR + 88,
                   B_XS = SM_BAR + 96, B_EMPTY = SM_BAR + 128, B_DONE = SM_BAR + 192, B_XE = SM_BAR + 200,
                   B_GUD = SM_BAR + 224, B_OE = B_GUD + 8, B_OT = B_GUD + 40, B_MOD = B_GUD + 72,
                   B_GU = SM_BAR + 104, B_ALL = SM_BAR + 112, B_UP = SM_BAR + 120, B_DN = B_GUD + 80, B_RS = B_GUD + 88, B_INIT = B_GUD + 96,
                   B_RE = B_GUD + 104, B_G2 = B_GUD + 112, B_DD = B_GUD + 176, B_HF = B_GUD + 184;

struct Params {
    CUtensorMap x, x2, w, wr, woa, wob, xg, gate, up, up2, down;
    __nv_bfloat16* op;
    const __nv_bfloat16 *xp, *upp, *w_r, *gate_w;
};

constexpr int SC_O = 0;
constexpr int SC_HALO = 1280;
constexpr int SC_GU = 1440;
constexpr int SC_Y = 1504;
constexpr int SC_SIZE = 1600;
__device__ __align__(128) uint4 g_sc[NCTA * SC_SIZE];
__device__ __align__(128) uint4 g_cand[NCTA];
__device__ __align__(16) uint32_t g_gate[2048];
__device__ __align__(128) unsigned g_cnt[64];
#define TSM(i) do { } while (0)
#define TS(i) do { } while (0)
#define TS2(i) do { } while (0)
#define TSX(i) do { } while (0)

__device__ __forceinline__ uint32_t smem_u32(const void* p) { return (uint32_t)__cvta_generic_to_shared(p); }
__device__ __forceinline__ void fault() { asm volatile("st.shared.u32 [%0], %0;" ::"r"(0x100001) : "memory"); }
__device__ __forceinline__ void mbar_init(uint32_t bar, uint32_t cnt) {
    asm volatile("mbarrier.init.shared::cta.b64 [%0], %1;" ::"r"(bar), "r"(cnt) : "memory");
}
__device__ __forceinline__ void mbar_expect_tx(uint32_t bar, uint32_t bytes) {
    asm volatile("mbarrier.arrive.expect_tx.shared::cta.b64 _, [%0], %1;" ::"r"(bar), "r"(bytes) : "memory");
}
__device__ __forceinline__ void mbar_arrive(uint32_t bar) {
    asm volatile("mbarrier.arrive.shared::cta.b64 _, [%0];" ::"r"(bar) : "memory");
}
__device__ __forceinline__ bool mbar_try(uint32_t bar, uint32_t parity) {
    uint32_t ok;
    asm volatile("{\n.reg .pred p;\nmbarrier.try_wait.parity.shared::cta.b64 p, [%1], %2;\nselp.u32 %0, 1, 0, p;\n}"
                 : "=r"(ok) : "r"(bar), "r"(parity) : "memory");
    return ok;
}
__device__ __forceinline__ void mbar_wait(uint32_t bar, uint32_t parity) {
    asm volatile("{\n.reg .pred p;\nAGAIN:\nmbarrier.try_wait.parity.shared::cta.b64 p, [%0], %1;\n@!p bra AGAIN;\n}"
                 ::"r"(bar), "r"(parity) : "memory");
}
__device__ __forceinline__ void tma_2d(uint32_t dst, const CUtensorMap* m, uint32_t bar, int c0, int c1) {
    asm volatile("cp.async.bulk.tensor.2d.shared::cluster.global.mbarrier::complete_tx::bytes [%0], [%1, {%3, %4}], [%2];"
                 ::"r"(dst), "l"(m), "r"(bar), "r"(c0), "r"(c1) : "memory");
}
__device__ __forceinline__ void bulk_load(uint32_t dst, const void* src, uint32_t bytes, uint32_t bar) {
    asm volatile("cp.async.bulk.shared::cluster.global.mbarrier::complete_tx::bytes [%0], [%1], %2, [%3];"
                 ::"r"(dst), "l"(src), "r"(bytes), "r"(bar) : "memory");
}
__device__ __forceinline__ void bulk_store(void* dst, uint32_t src, uint32_t bytes) {
    asm volatile("cp.async.bulk.global.shared::cta.bulk_group [%0], [%1], %2;" ::"l"(dst), "r"(src), "r"(bytes) : "memory");
}
__device__ __forceinline__ void tma_3d(uint32_t dst, const CUtensorMap* m, uint32_t bar, int c0, int c1, int c2) {
    asm volatile("cp.async.bulk.tensor.3d.shared::cluster.global.mbarrier::complete_tx::bytes [%0], [%1, {%3, %4, %5}], [%2];"
                 ::"r"(dst), "l"(m), "r"(bar), "r"(c0), "r"(c1), "r"(c2) : "memory");
}
__device__ __forceinline__ void fence_async_smem() { asm volatile("fence.proxy.async.shared::cta;" ::: "memory"); }
__device__ __forceinline__ void wg_fence() { asm volatile("wgmma.fence.sync.aligned;" ::: "memory"); }
__device__ __forceinline__ void wg_commit() { asm volatile("wgmma.commit_group.sync.aligned;" ::: "memory"); }
template <int N> __device__ __forceinline__ void wg_wait() { asm volatile("wgmma.wait_group.sync.aligned %0;" ::"n"(N) : "memory"); }
__device__ __forceinline__ void bar_sync(int id, int n) { asm volatile("bar.cta.sync %0, %1;" ::"r"(id), "r"(n) : "memory"); }
__device__ __forceinline__ void bar_arrive(int id, int n) { asm volatile("bar.cta.arrive %0, %1;" ::"r"(id), "r"(n) : "memory"); }

__device__ constexpr uint32_t desc_lo(uint32_t addr, uint32_t lbo) { return (addr >> 4) | ((lbo >> 4) << 16); }
__device__ __forceinline__ bool elect_one() {
    uint32_t p;
    asm volatile("{\n.reg .pred p;\nelect.sync _|p, 0xffffffff;\nselp.u32 %0, 1, 0, p;\n}" : "=r"(p));
    return p;
}
__device__ __forceinline__ uint32_t ld_relaxed4(const void* p) {
    uint32_t v;
    asm volatile("ld.relaxed.gpu.global.u32 %0, [%1];" : "=r"(v) : "l"(p) : "memory");
    return v;
}
__device__ __forceinline__ void st_relaxed4(void* p, uint32_t v) {
    asm volatile("st.relaxed.gpu.global.u32 [%0], %1;" ::"l"(p), "r"(v) : "memory");
}
__device__ __forceinline__ void red_inc(unsigned* p, unsigned after) {
    asm volatile("red.relaxed.gpu.global.add.u32 [%0], 1;" ::"l"(p), "r"(after) : "memory");
}
__device__ __forceinline__ uint32_t lds4(uint32_t a) {
    uint32_t v;
    asm volatile("ld.shared.u32 %0, [%1];" : "=r"(v) : "r"(a) : "memory");
    return v;
}
__device__ __forceinline__ void sts4(uint32_t a, uint32_t v) { asm volatile("st.shared.u32 [%0], %1;" ::"r"(a), "r"(v) : "memory"); }
__device__ __forceinline__ uint32_t hadd2(uint32_t a, uint32_t b) {
    uint32_t d;
    asm("add.rn.bf16x2 %0, %1, %2;" : "=r"(d) : "r"(a), "r"(b));
    return d;
}
__device__ __forceinline__ uint32_t hfma2(uint32_t a, uint32_t b, uint32_t c) {
    uint32_t d;
    asm("fma.rn.bf16x2 %0, %1, %2, %3;" : "=r"(d) : "r"(a), "r"(b), "r"(c));
    return d;
}
__device__ __forceinline__ uint4 ld_relaxed16(const void* p) {
    uint4 v;
    asm volatile("{\n.reg .b128 t;\n.reg .b64 lo, hi;\nld.relaxed.gpu.global.b128 t, [%4];\nmov.b128 {lo, hi}, t;\n"
                 "mov.b64 {%0, %1}, lo;\nmov.b64 {%2, %3}, hi;\n}" : "=r"(v.x), "=r"(v.y), "=r"(v.z), "=r"(v.w) : "l"(p) : "memory");
    return v;
}
__device__ __forceinline__ void st_relaxed16(void* p, uint32_t a, uint32_t b, uint32_t c, uint32_t d) {
    uint64_t lo = (uint64_t)a | ((uint64_t)b << 32), hi = (uint64_t)c | ((uint64_t)d << 32);
    asm volatile("{\n.reg .b128 t;\nmov.b128 t, {%1, %2};\nst.relaxed.gpu.global.b128 [%0], t;\n}" ::"l"(p), "l"(lo), "l"(hi) : "memory");
}
__device__ __forceinline__ uint4 lds16(uint32_t a) {
    uint4 v;
    asm volatile("ld.shared.v4.u32 {%0, %1, %2, %3}, [%4];" : "=r"(v.x), "=r"(v.y), "=r"(v.z), "=r"(v.w) : "r"(a) : "memory");
    return v;
}
__device__ __forceinline__ void sts16(uint32_t a, uint32_t x, uint32_t y, uint32_t z, uint32_t w) {
    asm volatile("st.shared.v4.u32 [%0], {%1, %2, %3, %4};" ::"r"(a), "r"(x), "r"(y), "r"(z), "r"(w) : "memory");
}
__device__ __forceinline__ uint32_t pack2(float lo, float hi) {
    uint32_t r;
    asm("cvt.rn.bf16x2.f32 %0, %1, %2;" : "=r"(r) : "f"(hi), "f"(lo));
    return r;
}
__device__ __forceinline__ uint32_t pack2v(float lo, float hi) {
    uint32_t r;
    asm volatile("cvt.rn.bf16x2.f32 %0, %1, %2;" : "=r"(r) : "f"(hi), "f"(lo));
    return r;
}
__device__ __forceinline__ uint32_t shl(uint32_t v, uint32_t n) {
    uint32_t r;
    asm("shl.b32 %0, %1, %2;" : "=r"(r) : "r"(v), "r"(n));
    return r;
}
__device__ __forceinline__ float bf_lo(uint32_t u) { return __uint_as_float(u << 16); }
__device__ __forceinline__ float bf_hi(uint32_t u) { return __uint_as_float(u & 0xFFFF0000u); }
__device__ __forceinline__ float bf_round(float f) { return __bfloat162float(__float2bfloat16_rn(f)); }
__device__ __forceinline__ uint32_t movm(uint32_t a) {
    uint32_t d;
    asm volatile("movmatrix.sync.aligned.m8n8.trans.b16 %0, %1;" : "=r"(d) : "r"(a));
    return d;
}
__device__ __forceinline__ void mma16(float (&c)[4], uint32_t a0, uint32_t a1, uint32_t a2, uint32_t a3, uint32_t b0, uint32_t b1) {
    asm volatile("mma.sync.aligned.m16n8k16.row.col.f32.bf16.bf16.f32 {%0,%1,%2,%3}, {%4,%5,%6,%7}, {%8,%9}, {%0,%1,%2,%3};"
                 : "+f"(c[0]), "+f"(c[1]), "+f"(c[2]), "+f"(c[3]) : "r"(a0), "r"(a1), "r"(a2), "r"(a3), "r"(b0), "r"(b1));
}
__device__ __forceinline__ void mma8(float (&c)[4], uint32_t a0, uint32_t a1, uint32_t b0) {
    asm volatile("mma.sync.aligned.m16n8k8.row.col.f32.bf16.bf16.f32 {%0,%1,%2,%3}, {%4,%5}, {%6}, {%0,%1,%2,%3};"
                 : "+f"(c[0]), "+f"(c[1]), "+f"(c[2]), "+f"(c[3]) : "r"(a0), "r"(a1), "r"(b0));
}
__device__ __forceinline__ float ex2(float x) { float y; asm("ex2.approx.ftz.f32 %0, %1;" : "=f"(y) : "f"(x)); return y; }
__device__ __forceinline__ float rcp(float x) { float y; asm("rcp.approx.ftz.f32 %0, %1;" : "=f"(y) : "f"(x)); return y; }
__device__ __forceinline__ float sigmoidf(float z) { return rcp(1.0f + ex2(z * -1.4426950408889634f)); }
__device__ __forceinline__ float u2f(uint32_t u) { return __uint_as_float(u); }
__device__ __forceinline__ uint32_t f2u(float f) { return __float_as_uint(f); }

__device__ __forceinline__ void wgmma_main(float (&d)[96], uint32_t a, uint32_t b, int scale_d) {
    asm volatile("{\n.reg .pred p;\n.reg .b64 da, db;\nsetp.ne.b32 p, %98, 0;\n"
        "mov.b64 da, {%96, 0x40000040};\nmov.b64 db, {%97, 0x40000040};\n"
        "wgmma.mma_async.sync.aligned.m64n192k16.f32.bf16.bf16 "
        "{%0, %1, %2, %3, %4, %5, %6, %7, %8, %9, %10, %11, %12, %13, %14, %15, "
        "%16, %17, %18, %19, %20, %21, %22, %23, %24, %25, %26, %27, %28, %29, %30, %31, "
        "%32, %33, %34, %35, %36, %37, %38, %39, %40, %41, %42, %43, %44, %45, %46, %47, "
        "%48, %49, %50, %51, %52, %53, %54, %55, %56, %57, %58, %59, %60, %61, %62, %63, "
        "%64, %65, %66, %67, %68, %69, %70, %71, %72, %73, %74, %75, %76, %77, %78, %79, "
        "%80, %81, %82, %83, %84, %85, %86, %87, %88, %89, %90, %91, %92, %93, %94, %95}, "
        "da, db, p, 1, 1, 0, 1;\n}\n"
        : "+f"(d[0]), "+f"(d[1]), "+f"(d[2]), "+f"(d[3]), "+f"(d[4]), "+f"(d[5]), "+f"(d[6]), "+f"(d[7]),
          "+f"(d[8]), "+f"(d[9]), "+f"(d[10]), "+f"(d[11]), "+f"(d[12]), "+f"(d[13]), "+f"(d[14]), "+f"(d[15]),
          "+f"(d[16]), "+f"(d[17]), "+f"(d[18]), "+f"(d[19]), "+f"(d[20]), "+f"(d[21]), "+f"(d[22]), "+f"(d[23]),
          "+f"(d[24]), "+f"(d[25]), "+f"(d[26]), "+f"(d[27]), "+f"(d[28]), "+f"(d[29]), "+f"(d[30]), "+f"(d[31]),
          "+f"(d[32]), "+f"(d[33]), "+f"(d[34]), "+f"(d[35]), "+f"(d[36]), "+f"(d[37]), "+f"(d[38]), "+f"(d[39]),
          "+f"(d[40]), "+f"(d[41]), "+f"(d[42]), "+f"(d[43]), "+f"(d[44]), "+f"(d[45]), "+f"(d[46]), "+f"(d[47]),
          "+f"(d[48]), "+f"(d[49]), "+f"(d[50]), "+f"(d[51]), "+f"(d[52]), "+f"(d[53]), "+f"(d[54]), "+f"(d[55]),
          "+f"(d[56]), "+f"(d[57]), "+f"(d[58]), "+f"(d[59]), "+f"(d[60]), "+f"(d[61]), "+f"(d[62]), "+f"(d[63]),
          "+f"(d[64]), "+f"(d[65]), "+f"(d[66]), "+f"(d[67]), "+f"(d[68]), "+f"(d[69]), "+f"(d[70]), "+f"(d[71]),
          "+f"(d[72]), "+f"(d[73]), "+f"(d[74]), "+f"(d[75]), "+f"(d[76]), "+f"(d[77]), "+f"(d[78]), "+f"(d[79]),
          "+f"(d[80]), "+f"(d[81]), "+f"(d[82]), "+f"(d[83]), "+f"(d[84]), "+f"(d[85]), "+f"(d[86]), "+f"(d[87]),
          "+f"(d[88]), "+f"(d[89]), "+f"(d[90]), "+f"(d[91]), "+f"(d[92]), "+f"(d[93]), "+f"(d[94]), "+f"(d[95])
        : "r"(a), "r"(b), "r"(scale_d));
}

__device__ __forceinline__ void wgmma_rem(float (&d)[24], uint32_t a, uint32_t b, int scale_d) {
    asm volatile("{\n.reg .pred p;\n.reg .b64 da, db;\nsetp.ne.b32 p, %26, 0;\n"
        "mov.b64 da, {%24, 0x40000040};\nmov.b64 db, {%25, 0xC0000010};\n"
        "wgmma.mma_async.sync.aligned.m64n48k16.f32.bf16.bf16 "
        "{%0, %1, %2, %3, %4, %5, %6, %7, %8, %9, %10, %11, %12, %13, %14, %15, "
        "%16, %17, %18, %19, %20, %21, %22, %23}, "
        "da, db, p, 1, 1, 0, 1;\n}\n"
        : "+f"(d[0]), "+f"(d[1]), "+f"(d[2]), "+f"(d[3]), "+f"(d[4]), "+f"(d[5]), "+f"(d[6]), "+f"(d[7]),
          "+f"(d[8]), "+f"(d[9]), "+f"(d[10]), "+f"(d[11]), "+f"(d[12]), "+f"(d[13]), "+f"(d[14]), "+f"(d[15]),
          "+f"(d[16]), "+f"(d[17]), "+f"(d[18]), "+f"(d[19]), "+f"(d[20]), "+f"(d[21]), "+f"(d[22]), "+f"(d[23])
        : "r"(a), "r"(b), "r"(scale_d));
}

__device__ __forceinline__ void wgmma_out64(float (&d)[80], uint32_t a, uint32_t b, int scale_d) {
    asm volatile("{\n.reg .pred p;\n.reg .b64 da, db;\nsetp.ne.b32 p, %34, 0;\n"
        "mov.b64 da, {%32, 0x50};\nmov.b64 db, {%33, 0x40000040};\n"
        "wgmma.mma_async.sync.aligned.m64n64k16.f32.bf16.bf16 "
        "{%0, %1, %2, %3, %4, %5, %6, %7, %8, %9, %10, %11, %12, %13, %14, %15, "
        "%16, %17, %18, %19, %20, %21, %22, %23, %24, %25, %26, %27, %28, %29, %30, %31}, "
        "da, db, p, 1, 1, 0, 1;\n}\n"
        : "+f"(d[0]), "+f"(d[1]), "+f"(d[2]), "+f"(d[3]), "+f"(d[4]), "+f"(d[5]), "+f"(d[6]), "+f"(d[7]),
          "+f"(d[8]), "+f"(d[9]), "+f"(d[10]), "+f"(d[11]), "+f"(d[12]), "+f"(d[13]), "+f"(d[14]), "+f"(d[15]),
          "+f"(d[16]), "+f"(d[17]), "+f"(d[18]), "+f"(d[19]), "+f"(d[20]), "+f"(d[21]), "+f"(d[22]), "+f"(d[23]),
          "+f"(d[24]), "+f"(d[25]), "+f"(d[26]), "+f"(d[27]), "+f"(d[28]), "+f"(d[29]), "+f"(d[30]), "+f"(d[31])
        : "r"(a), "r"(b), "r"(scale_d));
}
__device__ __forceinline__ void wgmma_out96(float (&d)[80], uint32_t a, uint32_t b, int scale_d) {
    asm volatile("{\n.reg .pred p;\n.reg .b64 da, db;\nsetp.ne.b32 p, %50, 0;\n"
        "mov.b64 da, {%48, 0x50};\nmov.b64 db, {%49, 0x40000040};\n"
        "wgmma.mma_async.sync.aligned.m64n96k16.f32.bf16.bf16 "
        "{%0, %1, %2, %3, %4, %5, %6, %7, %8, %9, %10, %11, %12, %13, %14, %15, "
        "%16, %17, %18, %19, %20, %21, %22, %23, %24, %25, %26, %27, %28, %29, %30, %31, "
        "%32, %33, %34, %35, %36, %37, %38, %39, %40, %41, %42, %43, %44, %45, %46, %47}, "
        "da, db, p, 1, 1, 0, 1;\n}\n"
        : "+f"(d[32]), "+f"(d[33]), "+f"(d[34]), "+f"(d[35]), "+f"(d[36]), "+f"(d[37]), "+f"(d[38]), "+f"(d[39]),
          "+f"(d[40]), "+f"(d[41]), "+f"(d[42]), "+f"(d[43]), "+f"(d[44]), "+f"(d[45]), "+f"(d[46]), "+f"(d[47]),
          "+f"(d[48]), "+f"(d[49]), "+f"(d[50]), "+f"(d[51]), "+f"(d[52]), "+f"(d[53]), "+f"(d[54]), "+f"(d[55]),
          "+f"(d[56]), "+f"(d[57]), "+f"(d[58]), "+f"(d[59]), "+f"(d[60]), "+f"(d[61]), "+f"(d[62]), "+f"(d[63]),
          "+f"(d[64]), "+f"(d[65]), "+f"(d[66]), "+f"(d[67]), "+f"(d[68]), "+f"(d[69]), "+f"(d[70]), "+f"(d[71]),
          "+f"(d[72]), "+f"(d[73]), "+f"(d[74]), "+f"(d[75]), "+f"(d[76]), "+f"(d[77]), "+f"(d[78]), "+f"(d[79])
        : "r"(a), "r"(b), "r"(scale_d));
}
__device__ __forceinline__ void wgmma_reg64(float (&d)[80], uint32_t a0, uint32_t a1, uint32_t a2, uint32_t a3, uint32_t b, int scale_d) {
    asm volatile("{\n.reg .pred p;\n.reg .b64 db;\nsetp.ne.b32 p, %37, 0;\nmov.b64 db, {%36, 0x40000040};\n"
        "wgmma.mma_async.sync.aligned.m64n64k16.f32.bf16.bf16 "
        "{%0, %1, %2, %3, %4, %5, %6, %7, %8, %9, %10, %11, %12, %13, %14, %15, "
        "%16, %17, %18, %19, %20, %21, %22, %23, %24, %25, %26, %27, %28, %29, %30, %31}, "
        "{%32, %33, %34, %35}, db, p, 1, 1, 1;\n}\n"
        : "+f"(d[0]), "+f"(d[1]), "+f"(d[2]), "+f"(d[3]), "+f"(d[4]), "+f"(d[5]), "+f"(d[6]), "+f"(d[7]),
          "+f"(d[8]), "+f"(d[9]), "+f"(d[10]), "+f"(d[11]), "+f"(d[12]), "+f"(d[13]), "+f"(d[14]), "+f"(d[15]),
          "+f"(d[16]), "+f"(d[17]), "+f"(d[18]), "+f"(d[19]), "+f"(d[20]), "+f"(d[21]), "+f"(d[22]), "+f"(d[23]),
          "+f"(d[24]), "+f"(d[25]), "+f"(d[26]), "+f"(d[27]), "+f"(d[28]), "+f"(d[29]), "+f"(d[30]), "+f"(d[31])
        : "r"(a0), "r"(a1), "r"(a2), "r"(a3), "r"(b), "r"(scale_d));
}
__device__ __forceinline__ void wgmma_reg96(float (&d)[80], uint32_t a0, uint32_t a1, uint32_t a2, uint32_t a3, uint32_t b, int scale_d) {
    asm volatile("{\n.reg .pred p;\n.reg .b64 db;\nsetp.ne.b32 p, %53, 0;\nmov.b64 db, {%52, 0x40000040};\n"
        "wgmma.mma_async.sync.aligned.m64n96k16.f32.bf16.bf16 "
        "{%0, %1, %2, %3, %4, %5, %6, %7, %8, %9, %10, %11, %12, %13, %14, %15, "
        "%16, %17, %18, %19, %20, %21, %22, %23, %24, %25, %26, %27, %28, %29, %30, %31, "
        "%32, %33, %34, %35, %36, %37, %38, %39, %40, %41, %42, %43, %44, %45, %46, %47}, "
        "{%48, %49, %50, %51}, db, p, 1, 1, 1;\n}\n"
        : "+f"(d[32]), "+f"(d[33]), "+f"(d[34]), "+f"(d[35]), "+f"(d[36]), "+f"(d[37]), "+f"(d[38]), "+f"(d[39]),
          "+f"(d[40]), "+f"(d[41]), "+f"(d[42]), "+f"(d[43]), "+f"(d[44]), "+f"(d[45]), "+f"(d[46]), "+f"(d[47]),
          "+f"(d[48]), "+f"(d[49]), "+f"(d[50]), "+f"(d[51]), "+f"(d[52]), "+f"(d[53]), "+f"(d[54]), "+f"(d[55]),
          "+f"(d[56]), "+f"(d[57]), "+f"(d[58]), "+f"(d[59]), "+f"(d[60]), "+f"(d[61]), "+f"(d[62]), "+f"(d[63]),
          "+f"(d[64]), "+f"(d[65]), "+f"(d[66]), "+f"(d[67]), "+f"(d[68]), "+f"(d[69]), "+f"(d[70]), "+f"(d[71]),
          "+f"(d[72]), "+f"(d[73]), "+f"(d[74]), "+f"(d[75]), "+f"(d[76]), "+f"(d[77]), "+f"(d[78]), "+f"(d[79])
        : "r"(a0), "r"(a1), "r"(a2), "r"(a3), "r"(b), "r"(scale_d));
}
__device__ __forceinline__ void wgmma_reg(float (&d)[80], uint32_t a0, uint32_t a1, uint32_t a2, uint32_t a3, uint32_t b, int scale_d) {
    wgmma_reg64(d, a0, a1, a2, a3, b, scale_d);
    wgmma_reg96(d, a0, a1, a2, a3, b + 640, scale_d);
}
#define TSQ(i) do { } while (0)
#define TSR(i) do { } while (0)
#define MAP_TILE(b) (((b) & 1) | (((b) >> 1) & 2) | (((b) >> 5) << 2))
#define MAP_HG(b) (((((b) >> 2) & 6) ^ (((b) & 32) ? 2 : 4)) | ((((b) >> 1) ^ ((b) >> 2) ^ ((b) >> 3) ^ ((b) >> 5) ^ 1) & 1))
#define SKEW 4
#define PACE 500
#define PACE_W0 (-600)
#define PACE_A 100
#define PACE_XA 25
#define T_SH 150
#define PACE_B 450
#define RG_T0 1700
#define RG_DT 200
#define GU_T0 3600
#define GU_DT 500
#define RS_T0 9200
#define RS_DT 200
#define HALO_D 250
#define PF_UP 7000
#define PF_DT 450
#define O_D 250
#define O_DT 300
#define C1_D 0
#define C2_D 0
#define C5_D 0
#define C6_D 100
#define C7_D 100
#define GH_DT 300
#define GX_D 400
#define Y_AT 1
#define CAND_T 8100
#define DN_D 0
#define GATE_T 9000
#define GH_T0 6800
#define NRS 2
#define DN0(q) ((q) * 3 - ((q) == 3))
#define WO_D ((uint64_t)(C1_D / 16) << 8 | (uint64_t)(C2_D / 16) * 0x10101 << 16 | (uint64_t)(C5_D / 16) << 40 | (uint64_t)(C6_D / 16) << 48 | (uint64_t)(C7_D / 16) << 56)

__device__ __forceinline__ unsigned block_id() { unsigned b; asm volatile("mov.u32 %0, %%ctaid.x;" : "=r"(b)); return b; }
__device__ __forceinline__ uint32_t keep(uint32_t v) { return __shfl_sync(0xffffffffu, v, threadIdx.x); }
__device__ __forceinline__ uint32_t ukeep(uint32_t v) { return __shfl_sync(0xffffffffu, v, 0); }
__device__ __forceinline__ void ldsm2(uint32_t* d, uint32_t a) {
    asm volatile("ldmatrix.sync.aligned.m8n8.x4.shared.b16 {%0,%1,%2,%3}, [%8];\nldmatrix.sync.aligned.m8n8.x4.shared.b16 {%4,%5,%6,%7}, [%9];"
                 : "=r"(d[0]), "=r"(d[1]), "=r"(d[2]), "=r"(d[3]), "=r"(d[4]), "=r"(d[5]), "=r"(d[6]), "=r"(d[7])
                 : "r"(a), "r"(a ^ 32) : "memory");
}
__device__ __forceinline__ void stsm(uint32_t a, uint32_t x, uint32_t y, uint32_t z, uint32_t w) {
    asm volatile("stmatrix.sync.aligned.m8n8.x4.shared.b16 [%0], {%1,%2,%3,%4};" ::"r"(a), "r"(x), "r"(y), "r"(z), "r"(w) : "memory");
}
__device__ __forceinline__ void row_sums(float& sa, float& sb, float a0, float a1, float b0, float b1) {
    asm volatile("{\n.reg .f32 x, y;\nmma.sync.aligned.m16n8k8.row.col.f32.tf32.tf32.f32 {%0,x,%1,y}, {%2,%3,%4,%5}, {%6,%6}, {%7,%7,%7,%7};\n}"
                 : "=f"(sa), "=f"(sb) : "r"(f2u(a0)), "r"(f2u(b0)), "r"(f2u(a1)), "r"(f2u(b1)), "r"(0x3F800000), "f"(0.f));
}
template <bool SWP, int SEG, int E>
__device__ __forceinline__ void pack_blocks(uint32_t (&d)[10], const float (&am)[96], const float (&ar)[24]) {
#pragma unroll
    for (int t = 0; t < 10; t++) {
        const float* p = (SWP ? t < 2 : t >= 8) ? ar + (SEG * 2 + (t & 1)) * 4 + E : am + (SEG * 8 + t - (SWP ? 2 : 0)) * 4 + E;
        d[t] = pack2v(p[0], p[1]);
    }
}
#define HALF(hg) ((hg) >> 2)
#define CB(hg) ((hg) & 3)
__device__ __forceinline__ int src_of(int i, int hg) {
    return i == 0 ? hg : (i - (i <= (hg | 4))) ^ (~hg & 4);
}

__device__ __forceinline__ uint32_t o_buf(int i) { return __byte_perm(0x5B000000u, 0x473D6F65u, i) << 10; }
__device__ constexpr uint32_t wo_buf(int i) { return SM_W + ((0x10546103u >> i * 4) & 7) * 30720; }

template <int N>
__device__ __forceinline__ void poll(uint4 (&a)[N], const uint4* p, int stride) {
    bool bad;
    do {
        bad = false;
#pragma unroll
        for (int s = 0; s < N; s++) a[s] = ld_relaxed16(p + s * stride);
#pragma unroll
        for (int s = 0; s < N; s++) bad |= a[s].w == SENT;
    } while (__any_sync(0xffffffffu, bad));
}
__device__ __forceinline__ void pace(unsigned t0, int t) {
    asm volatile("{\n.reg .pred p;\n.reg .s32 d;\nAGAIN:\nmov.u32 d, %%clock;\nsub.s32 d, d, %0;\nsetp.lt.s32 p, d, 0;\n"
                 "@p nanosleep.u32 20;\n@p bra AGAIN;\n}" ::"r"(t0 + t) : "memory");
}
__device__ __forceinline__ void l2_prefetch(const void* p) { asm volatile("prefetch.global.L2 [%0];" ::"l"(p) : "memory"); }

template <int ROW>
__device__ __forceinline__ void wgmma_vec(float (&d)[8], uint32_t a, uint32_t b, int scale_d) {
    asm volatile("{\n.reg .pred p;\n.reg .b64 da, db;\nsetp.ne.b32 p, %10, 0;\nmov.b64 da, {%8, 0x40000040};\nmov.b64 db, {%9, %11};\n"
                 "wgmma.mma_async.sync.aligned.m64n16k16.f32.bf16.bf16 {%0, %1, %2, %3, %4, %5, %6, %7}, da, db, p, 1, 1, 1, 0;\n}"
                 : "+f"(d[0]), "+f"(d[1]), "+f"(d[2]), "+f"(d[3]), "+f"(d[4]), "+f"(d[5]), "+f"(d[6]), "+f"(d[7])
                 : "r"(a), "r"(b), "r"(scale_d), "n"(ROW / 16));
}

__global__ void __launch_bounds__(512, 1) fused_kernel(const __grid_constant__ Params P) {
    extern __shared__ __align__(1024) uint8_t smem_raw[];
    const unsigned t_start = clock() - T_SH;
    const int tid = threadIdx.x, lane = tid & 31;
    const unsigned b0 = block_id();
    if (tid == 384) {
        const int tile = MAP_TILE(b0), hg = MAP_HG(b0), swp = (hg & 3) == 3;
        mbar_init(B_FULL, 1);
        asm volatile("fence.mbarrier_init.release.cluster;" ::: "memory");
        sts4(SM_PROF + 63 * 4, clock());
        tma_3d(SM_X + 8192, &P.x, B_FULL, 0, tile & 1, (tile >> 1) * 128 + 64);
        tma_3d(SM_W, &P.w, B_FULL, hg * 80 + (swp ? 16 : 0), 0, 0);
        tma_3d(SM_W + 12288, &P.wr, B_FULL, hg * 80 + (swp ? 0 : 64), 0, 0);
        mbar_init(B_XL0, 1);
        mbar_init(B_FULL + 8, 1);
        mbar_init(B_FULL + 16, 1);
        asm volatile("fence.mbarrier_init.release.cluster;" ::: "memory");
        tma_3d(SM_X, &P.x, B_XL0, 0, tile & 1, (tile >> 1) * 128);
        mbar_expect_tx(B_FULL, 15360 + 8192);
        mbar_expect_tx(B_XL0, 8192);
    }
    const int warp = __shfl_sync(0xffffffffu, tid >> 5, 0);
    if (warp < 8 && (warp & 3) && elect_one()) {
#pragma unroll
        for (int i = 0; i < 4; i++) mbar_init(SM_BAR + (warp - (warp >> 2)) * 32 + i * 8, warp < 4 ? 1 : warp < 7 ? 2 : 4);
        asm volatile("fence.mbarrier_init.release.cluster;" ::: "memory");
    }
    __syncthreads();
    const unsigned bx = block_id();
    const int tile = MAP_TILE(bx), hg = MAP_HG(bx);
    const int cid = tile * 8 + hg;
    const int par = tile & 1, p0 = (tile >> 1) * 128;
    uint4* const sc = g_sc + cid * SC_SIZE;
    const int fid = ((bx - 8) & 127) ^ (~bx >> 1 & 2);
    const bool swp = (hg & 3) == 3;
    const int wcm = hg * 80 + (swp ? 16 : 0), wcr = hg * 80 + (swp ? 0 : 64);
    if (warp == 12 && elect_one()) {
        mbar_expect_tx(B_FULL + 8, 15360);
        tma_3d(SM_W + 15360, &P.w, B_FULL + 8, wcm, 32, 0);
        tma_3d(SM_W + 15360 + 12288, &P.wr, B_FULL + 8, wcr, 32, 0);
        mbar_expect_tx(B_FULL + 16, 15360 + 16384);
        tma_3d(SM_W + 30720, &P.w, B_FULL + 16, wcm, 64, 0);
        tma_3d(SM_W + 30720 + 12288, &P.wr, B_FULL + 16, wcr, 64, 0);
    }

    if (warp >= 12) {
        asm volatile("setmaxnreg.dec.sync.aligned.u32 32;");
        if (warp == 12) {
            if (elect_one()) {
#pragma unroll 1
                for (int s = 3; s < 20; s++) {
                    const uint32_t fb = B_FULL + (s & 7) * 8, dst = SM_W + (s & 7) * 15360;
                    mbar_wait(fb + (B_EMPTY - B_FULL), ~(s >> 3) & 1);
                    pace(t_start, max(PACE_A + s * PACE_B, PACE_W0 + s * PACE));
                    mbar_expect_tx(fb, (s & 1) ? 15360 : 15360 + 16384);
                    tma_3d(dst, &P.w, fb, wcm, s * 32, 0);
                    tma_3d(dst + 12288, &P.wr, fb, wcr, s * 32, 0);
                    TS2(20 + s);
                }
                mbar_wait(B_RG2, 0);
                if (fid < NFFN) {
                    const int nd = 3 - (fid >> 1 & 1);
                    mbar_expect_tx(B_UP, 6144);
                    mbar_expect_tx(B_DN, nd * 8192);
                    mbar_wait(B_EMPTY + 4 * 8, 1);
                    TSQ(40);
                    tma_2d(SM_UP, &P.up2, B_UP, (fid >> 2) * 64, (fid & 3) * 160 + 112);
                    mbar_wait(B_EMPTY + 5 * 8, 1);
                    const unsigned t0 = clock();
#pragma unroll 1
                    for (int i = 0; i < nd; i++) {
                        pace(t0, i * DN_D);
                        tma_3d(SM_DN + i * 8192, &P.down, B_DN, 0, (fid >> 2) * 64, DN0(fid & 3) + i);
                    }
                    TSQ(41);
                }
                const int cb = CB(hg), ca = (cb * 5 + 1) >> 1, cr = cb * 160 + ((cb & 1) ? 0 : 128);
                unsigned t1 = 0;
#pragma unroll 1
                for (int j = 0; j < 8; j++) {
                    const int i = j ^ (j == 3 || j == 4 ? 7 : 0);
                    if (j != 3) mbar_wait(j < 3 ? B_EMPTY + ((2 * j + 7) & 7) * 8 : j == 5 ? B_HF : B_GUD + (j - 4) * 8, j == 0);
                    if (j != 3 && j != 4) t1 = clock();
                    pace(t1, (WO_D >> j * 8 & 255) * 16);
                    const uint32_t dst = wo_buf(i), gb = B_G2 + i * 8;
                    TSQ(20 + j);
                    mbar_expect_tx(gb, 25600);
                    tma_3d(dst, &P.woa, gb, 0, src_of(i, hg) * 80, ca);
                    tma_2d(dst + 20480, &P.wob, gb, cr, src_of(i, hg) * 80);
                }
            }
        } else if (warp == 14) {
            if (elect_one()) {
#pragma unroll 1
                for (int kb = 1; kb < 10; kb++) {
                    const uint32_t fb = B_FULL + (kb & 3) * 16, dst = SM_X + (kb & 3) * 16384;
                    mbar_wait(fb + (B_EMPTY - B_FULL + 8), ~(kb >> 2) & 1);
                    if (kb >= 4) mbar_wait(B_XE + (kb - 4 >> 1) * 8, 0);
                    pace(t_start, max(PACE_XA + 2 * kb * PACE_B, PACE_W0 - 50 + (2 * kb + 1) * PACE));
                    tma_3d(dst, &P.x2, fb, kb * 64, par, p0);
                }
            }
            __syncwarp();
            mbar_wait(B_ALL, 0);
            bar_sync(12, 64);
            pace(t_start, 0);
            pace(clock(), HALO_D);
            uint4 hv[5];
            poll<5>(hv, sc + (SC_HALO - (tile < 2 ? 0 : 16 * SC_SIZE) + lane), 32);
#pragma unroll
            for (int s = 0; s < 5; s++) sts16(SM_HALO + s * 512 + lane * 16, hv[s].x, hv[s].y, hv[s].z, hv[s].w);
            bar_arrive(8, 64);
            TSM(25);
        } else if (warp == 15) {
            int it = smem_u32(smem_raw) == SB ? 0 : 1 << 20;
            while (!mbar_try(B_XE + 16, 0))
                if (++it > (1 << 20)) fault();
            TSR(44);
            const uint32_t key = lds4(SM_KEY + (lane & 15) * 4), epoch = lds4(SM_KEY + 20 * 4);
            uint32_t k1 = __reduce_max_sync(0xffffffffu, key);
            uint32_t k2 = __reduce_max_sync(0xffffffffu, key == k1 ? 0u : key);
            if (elect_one()) {
                st_relaxed16(g_cand + cid, k1, k2, epoch, epoch);
                red_inc(g_cnt, epoch);
                TSR(45);
                if (fid < NFFN) {
                    mbar_expect_tx(B_GU, 10240);
                    pace(t_start, GH_T0);
                    tma_2d(SM_G, &P.up, B_GU, (fid >> 2) * 64, (fid & 3) * 160 + 32);
                    pace(clock(), GH_DT);
                    tma_2d(SM_G + 4096, &P.up2, B_GU, (fid >> 2) * 64, (fid & 3) * 160 + 64);
                }
            }
            __syncwarp();
            pace(t_start, CAND_T);
            TSR(46);
            uint4 cd[4];
            do {
                TSR(47);
#pragma unroll
                for (int j = 0; j < 4; j++) cd[j] = ld_relaxed16(g_cand + lane + 32 * j);
                if (++it > (1 << 20)) fault();
            } while (!__all_sync(0xffffffffu, cd[0].z == epoch && cd[1].z == epoch && cd[2].z == epoch && cd[3].z == epoch));
            TSR(48);
            uint32_t l1 = 0, l2 = 0;
#pragma unroll
            for (int j = 0; j < 4; j++) {
                l2 = max(max(l2, cd[j].y), min(l1, cd[j].x));
                l1 = max(l1, cd[j].x);
            }
            k1 = __reduce_max_sync(0xffffffffu, l1);
            k2 = __reduce_max_sync(0xffffffffu, l1 == k1 ? l2 : l1);
            if (elect_one()) {
                bulk_load(SM_XS, P.xp + (~k1 & 2047) * 640 + (fid & 3) * 160, 320, B_XS);
                bulk_load(SM_XS + 320, P.xp + (~k2 & 2047) * 640 + (fid & 3) * 160, 320, B_XS);
                sts16(SM_KEY + 16 * 4, k1, k2, 0, 0);
                mbar_expect_tx(B_XS, 640);
                mbar_arrive(B_ALL);
                TSR(49);
            }
            __syncwarp();
            while (!mbar_try(B_DONE, 0) || !mbar_try(B_MOD, 0))
                if (++it > (1 << 20)) fault();
        } else {
#pragma unroll 1
            for (int i = 0; i < 10; i++) sts16(SM_SENT + i * 512 + lane * 16, SENT, SENT, SENT, SENT);
            fence_async_smem();
            __syncwarp();
            if (elect_one()) {
                mbar_expect_tx(B_RG, 2560);
                asm volatile("mbarrier.expect_tx.relaxed.cta.shared::cta.b64 [%0], 10240;" ::"r"(B_RG2) : "memory");
                asm volatile("mbarrier.expect_tx.relaxed.cta.shared::cta.b64 [%0], 24576;" ::"r"(B_GU) : "memory");
                bulk_load(SM_RED, P.w_r, 1280, B_RG);
                bulk_load(SM_RED + 1280, P.gate_w, 1280, B_RG);
#pragma unroll
                for (int i = 0; i < 24; i++) mbar_init(B_GUD + i * 8, i == 23 ? 8 : i == 0 || i == 22 ? 4 : i < 15 + NRS ? 1 : 2);
#pragma unroll 1
                for (int i = 0; i < 5; i++) {
                    pace(t_start, RG_T0 + i * RG_DT);
                    tma_3d(SM_G + i * 2048, &P.xg, B_RG2, 320 + i * 64, par, p0 + hg * 16);
                }
                bulk_store(sc + SC_HALO, SM_SENT, 5120);
                asm volatile("cp.async.bulk.commit_group;\ncp.async.bulk.wait_group 0;" ::: "memory");
                mbar_arrive(B_RG2);
                TS(43);
#pragma unroll 1
                for (int i = 0; i < (fid < NFFN ? 6 : 0); i++) {
                    pace(t_start, GU_T0 + i * GU_DT);
                    tma_2d(SM_F + i * 4096, i < 5 ? &P.gate : &P.up, B_GU, (fid >> 2) * 64, (fid & 3) * 160 + (i < 5 ? i * 32 : 0));
                }
            }
            __syncwarp();
            if (fid < NFFN) {
                const __nv_bfloat16* up = P.upp + ((fid & 3) * 160 + 112 + lane) * 1728 + (fid >> 2) * 64;
                pace(t_start, PF_UP - PF_DT);
                l2_prefetch(up);
                l2_prefetch(up + 16 * 1728);
            }
            const unsigned goal = (ld_relaxed4(g_cnt + 32) | (NCTA - 1)) + 1;
            if (elect_one()) {
#pragma unroll 1
                for (int i = 0; i < 4; i++) {
                    pace(t_start, RS_T0 + i * RS_DT);
                    bulk_store(sc + i * 320, SM_SENT, 5120);
                }
                asm volatile("cp.async.bulk.commit_group;\ncp.async.bulk.wait_group 0;" ::: "memory");
                red_inc(g_cnt + 32, goal);
                mbar_arrive(B_RS);
            }
            __syncwarp();
            TSQ(30);
            while (ld_relaxed4(g_cnt + 32) - goal > 0x80000000u) {}
            if (lane == 0) mbar_arrive(B_INIT);
            TS(45);
        }
    } else if (warp >= 8) {
        asm volatile("setmaxnreg.dec.sync.aligned.u32 96;");
        const int t = tid - 256;
        const unsigned epoch = ld_relaxed4(g_cnt) / NCTA + 1;
        float gv = 0.f;
        int grow = hg * 16 + (t >> 3);
        {
            const uint32_t sw = (t >> 4) * 128 + (((t ^ (t >> 4)) & 7) << 4), hi = (t >> 3) & 1;
            const uint32_t xs = keep(sw + SM_X + hi * 16384 + hg * 2048), xg = keep(sw + SM_G + hi * 2048), ws = SM_RED + (t & 15) * 16;
            uint4 a[5], b[5], w[5];
            float r0 = 0.f, r1 = 0.f;
            auto load = [&](int p, uint32_t xa) { a[p] = lds16(xa); b[p] = lds16(xa + 1024); w[p] = lds16(ws + p * 256); };
            auto dot = [&](int p) {
                const uint32_t as[4] = {a[p].x, a[p].y, a[p].z, a[p].w}, bs[4] = {b[p].x, b[p].y, b[p].z, b[p].w};
                const uint32_t vs[4] = {w[p].x, w[p].y, w[p].z, w[p].w};
#pragma unroll
                for (int e = 0; e < 4; e++) {
                    r0 = fmaf(bf_lo(as[e]), bf_lo(vs[e]), r0);
                    r1 = fmaf(bf_lo(bs[e]), bf_lo(vs[e]), r1);
                    r0 = fmaf(bf_hi(as[e]), bf_hi(vs[e]), r0);
                    r1 = fmaf(bf_hi(bs[e]), bf_hi(vs[e]), r1);
                }
                asm volatile("" : "+f"(r0), "+f"(r1), "+r"(a[p].x), "+r"(a[p].y), "+r"(a[p].z), "+r"(a[p].w),
                                  "+r"(b[p].x), "+r"(b[p].y), "+r"(b[p].z), "+r"(b[p].w));
            };
            auto release = [&](int p) {
                if (__ballot_sync(0xffffffffu, lane == 0 || (a[p].w ^ w[p].w) == b[p].w) && lane == 0) mbar_arrive(B_XE + p * 8);
            };
            auto total = [&]() {
                float r = (hi ? r1 : r0) + __shfl_xor_sync(0xffffffffu, hi ? r0 : r1, 8);
                r += __shfl_xor_sync(0xffffffffu, r, 4);
                r += __shfl_xor_sync(0xffffffffu, r, 2);
                return bf_round(r + __shfl_xor_sync(0xffffffffu, r, 1));
            };
            mbar_wait(B_RG, 0);
            mbar_wait(B_XL0, 0);
            mbar_wait(B_FULL, 0);
            mbar_wait(B_FULL + 16, 0);
            TSR(32);
            load(0, xs);
            release(0);
            dot(0);
            TSR(33);
            mbar_wait(B_RG2, 0);
            TSR(34);
            load(3, xg + 2048);
            load(4, xg + 6144);
            mbar_wait(B_FULL + 32, 0);
            mbar_wait(B_FULL + 48, 0);
            TSR(35);
            load(1, xs + 32768);
            dot(3);
            release(1);
            dot(4);
            TSR(36);
            mbar_wait(B_FULL, 1);
            TSR(37);
            load(2, hi ? xg - 2048 : xs);
            dot(1);
            dot(2);
            TSR(42);
            grow = hg * 16 + (t >> 4) + hi * 8;
            const uint32_t u = f2u(total());
            sts4(SM_KEY + (t >> 3) * 4, (((int)u < 0 ? ~u : u | 0x80000000u) & 0xFFFF0000u) | (2047 - (p0 + grow) * 2 - par));
            sts4(SM_KEY + 20 * 4, epoch);
            __syncwarp();
            if (lane == 0) mbar_arrive(B_XE + 16);
            TSR(43);
            r0 = r1 = 0.f;
#pragma unroll
            for (int p = 0; p < 5; p++) w[p] = lds16(ws + 1280 + p * 256);
#pragma unroll
            for (int p = 0; p < 5; p++) dot(p);
            gv = total();
        }
        if ((lane & 7) == 4) st_relaxed4(g_gate + tile * 128 + grow, f2u(bf_round(sigmoidf(gv))) | (epoch & 0xFFFFu));
        TSR(38);
        if (warp == 9) {
            pace(t_start, GATE_T);
            uint4 v;
            do {
                asm volatile("ld.relaxed.gpu.global.v4.u32 {%0, %1, %2, %3}, [%4];"
                             : "=r"(v.x), "=r"(v.y), "=r"(v.z), "=r"(v.w) : "l"(g_gate + tile * 128 + lane * 4) : "memory");
            } while (__any_sync(0xffffffffu, ((v.x ^ epoch) | (v.y ^ epoch) | (v.z ^ epoch) | (v.w ^ epoch)) & 0xFFFFu));
            sts16(SM_GATE + lane * 16, v.x & 0xFFFF0000u, v.y & 0xFFFF0000u, v.z & 0xFFFF0000u, v.w & 0xFFFF0000u);
            __syncwarp();
            if (lane == 0) mbar_arrive(B_GT);
        }
        mbar_wait(B_XS, 0);
        TS(warp == 8 ? 50 : 63);
        TSR(50);
        const int cq = lane & 3, q = fid & 3;
        if (fid < NFFN) {
            uint4* const sc = g_sc + fid * SC_SIZE;
            float ga[8], ua[8];
            mbar_wait(B_GU, 0);
            TS(warp == 8 ? 61 : 63);
            mbar_wait(B_UP, 0);
            TSR(52);
            bar_sync(13, 256);
            TSM(warp == 8 ? 53 : 63);
            wg_fence();
#pragma unroll
            for (int i = 0; i < 10; i++) {
                wgmma_vec<320>(ga, desc_lo(SM_F, 16) + i * 128, desc_lo(SM_XS, 16) + i * 2, i);
                wgmma_vec<320>(ua, desc_lo(i < 7 ? SM_F + 20480 : SM_UP - 14336, 16) + i * 128, desc_lo(SM_XS, 16) + i * 2, i);
            }
            wg_commit();
            wg_wait<0>();
            TSM(warp == 8 ? 54 : 63);
            if (cq == 0) {
                st_relaxed16(sc + SC_GU + (t >> 2), f2u(ga[0]), f2u(ga[2]), f2u(ga[4]), f2u(ga[6]));
                st_relaxed16(sc + SC_GU + 32 + (t >> 2), f2u(ua[0]), f2u(ua[2]), f2u(ua[4]), f2u(ua[6]));
            }
            if (lane == 0) mbar_arrive(B_GUD);
            uint4 pq[2];
            pace(clock(), GX_D);
            poll<2>(pq, sc + (cq - q) * SC_SIZE + SC_GU + (t >> 2), 32);
            TSR(55);
            const bool tk = cq & 2, c8 = cq & 1;
            float v[4];
#pragma unroll
            for (int m = 0; m < 2; m++) {
                v[2 * m] = u2f(tk ? pq[m].z : pq[m].x) + __shfl_xor_sync(0xffffffffu, u2f(tk ? pq[m].x : pq[m].z), 2);
                v[2 * m + 1] = u2f(tk ? pq[m].w : pq[m].y) + __shfl_xor_sync(0xffffffffu, u2f(tk ? pq[m].y : pq[m].w), 2);
                v[m] = bf_round((c8 ? v[2 * m + 1] : v[2 * m]) + __shfl_xor_sync(0xffffffffu, c8 ? v[2 * m] : v[2 * m + 1], 1));
            }
            const uint32_t h = pack2(bf_round(v[0] * sigmoidf(v[0])) * v[1], 0.f);
            asm volatile("st.shared.u16 [%0], %1;" ::"r"(SM_XS + (cq >> 1) * 128 + ((t >> 5) * 16 + (cq & 1) * 8 + (lane >> 2)) * 2),
                         "h"((uint16_t)h) : "memory");
            fence_async_smem();
            bar_sync(4, 128);
            TS(warp == 8 ? 57 : 63);
            mbar_wait(B_DN, 0);
            bar_sync(14, 384);
            TSR(56);
            float y[3][8];
#pragma unroll 1
            for (int i = 0; i < 4; i++) {
                wg_fence();
#pragma unroll
                for (int m = 0; m < 3; m++)
                    wgmma_vec<128>(y[m], desc_lo(SM_DN + m * 8192, 16) + i * 128, desc_lo(SM_XS, 16) + i * 2, i);
                wg_commit();
            }
            wg_wait<0>();
            if (cq == 0) {
#pragma unroll
                for (int m = 0; m < 6; m++)
                    asm volatile("st.relaxed.gpu.global.v2.f32 [%0], {%1, %2};"
                                 ::"l"(reinterpret_cast<float2*>(sc + SC_Y) + (m & 1) * 96 + (m >> 1) * 32 + (t >> 2)),
                                   "f"(y[m >> 1][(m & 1) * 4]), "f"(y[m >> 1][(m & 1) * 4 + 2]) : "memory");
            }
        } else if (lane == 0) {
            mbar_arrive(B_GUD);
        }
        if (lane == 0) mbar_arrive(B_DD);
        TSM(warp == 8 ? 51 : 63);
        const uint32_t k1 = lds4(SM_KEY + 16 * 4), k2 = lds4(SM_KEY + 17 * 4);
        const uint32_t mine = (tile >> 1) * 256 + HALF(hg) * 128 + par;
        const bool own1 = (~k1 & 0x781) == mine, own2 = (~k2 & 0x781) == mine;
        if ((own1 || own2) && NFFN) {
            const int rg = min(t / 40, 2), c40 = t % 40, un = CB(hg) * 40 + c40, src = un < 48 ? 0 : un < 96 ? 1 : un < 128 ? 2 : 3;
            const int col = min(t >> 3, 9) * 16 + (t & 1) * 8 + (t & 6);
            mbar_wait(B_OE + Y_AT * 8, 0);
            TS(warp == 8 ? 60 : 63);
#pragma unroll 1
            for (int j = !own1; j <= own2; j++) {
                const uint4* p = g_sc + (rg * 4 + src) * SC_SIZE + SC_Y + j * 48 + un - DN0(src) * 16;
                const uint32_t key = j ? k2 : k1;
                const uint32_t xv = *reinterpret_cast<const uint32_t*>(P.xp + (~key & 2047) * 640 + CB(hg) * 160 + col);
                float y[4];
                bool bad;
                do {
                    uint4 yp[9];
#pragma unroll
                    for (int i = 0; i < 9; i++) yp[i] = ld_relaxed16(p + i * 12 * SC_SIZE);
                    y[0] = y[1] = y[2] = y[3] = 0.f;
                    bad = false;
#pragma unroll
                    for (int i = 0; i < 9; i++) {
                        y[0] += u2f(yp[i].x); y[1] += u2f(yp[i].y); y[2] += u2f(yp[i].z); y[3] += u2f(yp[i].w);
                        bad |= max(max(yp[i].x, yp[i].y), max(yp[i].z, yp[i].w)) == SENT;
                    }
                } while (__any_sync(0xffffffffu, bad));
                TS(warp == 8 ? 62 : 63);
                sts16(SM_Y + j * 2048 + t * 16, f2u(y[0]), f2u(y[1]), f2u(y[2]), f2u(y[3]));
                bar_sync(4, 128);
                if (t < 80) {
                    const uint32_t ya = SM_Y + j * 2048 + (t >> 1) * 16 + (t & 1) * 4;
                    const float rs = bf_round(sigmoidf(u2f(((int)key < 0 ? key & 0x7FFFFFFFu : ~key) & 0xFFFF0000u)));
                    const float y0 = u2f(lds4(ya)) + u2f(lds4(ya + 640)) + u2f(lds4(ya + 1280));
                    const float y1 = u2f(lds4(ya + 8)) + u2f(lds4(ya + 648)) + u2f(lds4(ya + 1288));
                    sts4(SM_U + j * 320 + t * 4, hadd2(xv, pack2(bf_round(y0) * rs, bf_round(y1) * rs)));
                }
            }
            const int cc = col + (CB(hg) & 1 ? (col < 32 ? 128 : -32) : 0);
            mbar_wait(B_GT, 0);
#pragma unroll 1
            for (int j = !own1; j <= own2; j++) {
                const uint32_t tk = ~(j ? k2 : k1) & 2047, rr = tk >> 1 & 15, stg = SM_OUT + (tk >> 5 & 3) * 5120;
                const float n = 1.f - u2f(lds4(SM_GATE + (tk & 254) * 2));
                uint32_t u = lds4(SM_U + j * 320 + t * 4), nn = pack2(n, n), ca = stg + rr * 128 + (rr & 7) * 16;
                uint32_t aa = stg + (cc & 6) * 2 + (cc < 128 ? (cc >> 6) * 2048 + rr * 128 + (((cc >> 3 ^ rr) & 7) << 4)
                                                             : 4096 + rr * 64 + (((cc >> 3 ^ rr >> 1) & 3) << 4));
                __nv_bfloat16* dst = P.op + tk * 640 + CB(hg) * 160 + col;
                asm volatile("" : "+r"(u), "+r"(nn), "+r"(ca), "+r"(aa), "+l"(dst));
                mbar_wait(B_DONE, 0);
                const float chk = u2f(lds4(ca));
                uint32_t a = lds4(aa);
                if (chk != chk) {
                    mbar_wait(B_OE + 24, 0);
                    a = lds4(aa);
                }
                if (t < 80) *reinterpret_cast<uint32_t*>(dst) = hfma2(nn, u, a);
            }
        }
        if (t == 0) mbar_arrive(B_MOD);
        TS(warp == 8 ? 52 : 63);
    } else {
        asm volatile("setmaxnreg.inc.sync.aligned.u32 192;");
        const int wg = warp >> 2;
        const bool leader = (tid & 127) == 0;
        bool rel = false;
        uint32_t nb[40];
        const int odd = CB(hg) & 1, kba = ukeep(wg == HALF(hg) ? (CB(hg) * 5 + 1) >> 1 : 16), kbr = ukeep(kba + 2 - odd * 3);
        const int kbs = wg ? -1 : (20 - SKEW) / 2;
        const uint32_t xrow = keep(SM_X + (warp * 16 + (lane & 15)) * 128 + (((lane >> 4) ^ (lane & 7)) << 4));
        const int w4 = warp & 3, r = lane >> 2, cq = lane & 3;
        float am[96], ar[24];
        TSM(warp == 0 ? 3 : 63);
        if (wg == 0) mbar_wait(B_XL0, 0);
#pragma unroll 1
        for (int kb = 0; kb < 10; kb++) {
            const uint32_t fb = B_FULL + (kb & 3) * 16, wo = (kb & 3) * 1920, ph = (kb >> 2) & 1;
            const uint32_t xo = desc_lo(SM_X, 16) + wg * 512 + (kb & 3) * 1024;
#pragma unroll
            for (int h = 0; h < 2; h++) {
                mbar_wait(fb + h * 8, ph);
                if (kb == 0 && h == 0) TS(warp == 0 ? 0 : warp == 4 ? 16 : 63);
                TS2(warp == 4 ? kb * 2 + h : 63);
                if (h == 1) {
                    const uint32_t xa = xrow + (kb & 3) * 16384;
                    if (kb == kba) { ldsm2(nb, xa); ldsm2(nb + 8, xa ^ 64); }
                    if (kb == kba + 1) { ldsm2(nb + 16, xa); ldsm2(nb + 24, xa ^ 64); }
                    if (kb == kbr) ldsm2(nb + 32, xa ^ (odd * 64));
                }
                wg_wait<1>();
                if (rel) mbar_arrive(B_EMPTY + ((kb * 16 - 16) & 48) + h * 8);
                if (h == (SKEW & 1) && kb == kbs) bar_sync(5, 256);
                wg_fence();
                wgmma_main(am, xo + h * 4, desc_lo(SM_W + h * 15360, 4096) + wo, h || kb);
                wgmma_rem(ar, xo + h * 4, desc_lo(SM_W + h * 15360 + 12288, 1024) + wo, h || kb);
                wgmma_main(am, xo + h * 4 + 2, desc_lo(SM_W + h * 15360 + 2048, 4096) + wo, 1);
                wgmma_rem(ar, xo + h * 4 + 2, desc_lo(SM_W + h * 15360 + 12288 + 512, 1024) + wo, 1);
                wg_commit();
            }
            rel = leader;
        }
        if (wg == 1) bar_arrive(5, 256);
        if (wg == 0) bar_arrive(13, 256);
        mbar_wait(B_EMPTY + 7 * 8 - wg * 16, 1);
        wg_wait<0>();
        if (rel) mbar_arrive(B_EMPTY + 3 * 8);
        TSM(warp == 0 ? 2 : warp == 4 ? 18 : 63);

        uint32_t kl[10], kh[10], vl[10], vh[10], ql[10], qh[10], kp[10], vp[10];
        if (swp) {
            pack_blocks<true, 1, 2>(kh, am, ar);
            pack_blocks<true, 2, 2>(vh, am, ar);
        } else {
            pack_blocks<false, 1, 2>(kh, am, ar);
            pack_blocks<false, 2, 2>(vh, am, ar);
        }
        const uint32_t pbuf = (wg ? SM_HALO1 : SM_HALO) + w4 * 2560 + lane * 16;
        const uint32_t hbuf = warp == 3 ? SM_HALO1 + lane * 16 : pbuf + 2560;
        {
            const uint32_t ex[20] = {kh[0], kh[1], kh[3], kh[4], kh[5], kh[6], kh[8], kh[9], kh[2], kh[7],
                                     vh[0], vh[1], vh[2], vh[3], vh[4], vh[5], vh[6], vh[7], vh[8], vh[9]};
            if (warp == 7) {
                uint4* const hp = sc + SC_HALO + lane;
#pragma unroll
                for (int s = 0; s < 5; s++) st_relaxed16(hp + s * 32, ex[4 * s], ex[4 * s + 1], ex[4 * s + 2], ex[4 * s + 3]);
                bar_arrive(12, 64);
            } else {
#pragma unroll
                for (int s = 0; s < 5; s++) sts16(hbuf + s * 512, ex[4 * s], ex[4 * s + 1], ex[4 * s + 2], ex[4 * s + 3]);
            }
        }
        if (warp == 3) bar_arrive(11, 64);
        if (swp) {
            pack_blocks<true, 2, 0>(vl, am, ar);
            pack_blocks<true, 0, 0>(ql, am, ar);
            pack_blocks<true, 0, 2>(qh, am, ar);
            pack_blocks<true, 1, 0>(kl, am, ar);
        } else {
            pack_blocks<false, 2, 0>(vl, am, ar);
            pack_blocks<false, 0, 0>(ql, am, ar);
            pack_blocks<false, 0, 2>(qh, am, ar);
            pack_blocks<false, 1, 0>(kl, am, ar);
        }
#pragma unroll
        for (int t = 0; t < 10; t++) { vl[t] = movm(vl[t]); vh[t] = movm(vh[t]); }
        mbar_wait(B_RS, 0);
        mbar_wait(B_GT, 0);
        const float g0 = u2f(lds4(SM_GATE + warp * 64 + (lane & 28))), g1 = u2f(lds4(SM_GATE + 32 + warp * 64 + (lane & 28)));

        const bool no_prev = warp == 0 && tile < 2, low = cq < 2;
        const bool le0 = 2 * cq <= r, le1 = 2 * cq + 1 <= r;
        const uint32_t mle = (le0 ? 0xFFFFu : 0u) | (le1 ? 0xFFFF0000u : 0u);
        const float scl = 0.22360679774997896f * 1.4426950408889634f;
        uint32_t pl[4], ph[4], ol[10], oh[10], cl = 0;
        {
            float sl[4][4], sh[4][4], sp[4][4];
            bar_sync(6 + wg, 128);
            if (w4 == 0) bar_sync(8 + wg * 3, 64);
            {
                const uint4 a = lds16(pbuf), b = lds16(pbuf + 512), c = lds16(pbuf + 1024), d = lds16(pbuf + 1536), e = lds16(pbuf + 2048);
                kp[0] = a.x; kp[1] = a.y; kp[3] = a.z; kp[4] = a.w; kp[5] = b.x; kp[6] = b.y; kp[8] = b.z; kp[9] = b.w;
                kp[2] = c.x; kp[7] = c.y; vp[0] = c.z; vp[1] = c.w; vp[2] = d.x; vp[3] = d.y; vp[4] = d.z; vp[5] = d.w;
                vp[6] = e.x; vp[7] = e.y; vp[8] = e.z; vp[9] = e.w;
            }
#pragma unroll
            for (int h = 0; h < 4; h++) {
                const int ta = (h >> 1) * 5 + (h & 1) * 3, tc = (h >> 1) * 5 + 2;
                const uint32_t ml = low != (h & 1) ? ql[tc] : 0u, mh = low != (h & 1) ? qh[tc] : 0u;
#pragma unroll
                for (int e = 0; e < 4; e++) sl[h][e] = sh[h][e] = sp[h][e] = 0.f;
                mma16(sl[h], ql[ta], qh[ta], ql[ta + 1], qh[ta + 1], kl[ta], kl[ta + 1]);
                mma16(sh[h], ql[ta], qh[ta], ql[ta + 1], qh[ta + 1], kh[ta], kh[ta + 1]);
                mma8(sl[h], ml, mh, kl[tc]);
                mma8(sh[h], ml, mh, kh[tc]);
            }
#pragma unroll
            for (int h = 0; h < 4; h++) {
                const int ta = (h >> 1) * 5 + (h & 1) * 3, tc = (h >> 1) * 5 + 2;
                mma16(sp[h], ql[ta], qh[ta], ql[ta + 1], qh[ta + 1], kp[ta], kp[ta + 1]);
                mma8(sp[h], low != (h & 1) ? ql[tc] : 0u, low != (h & 1) ? qh[tc] : 0u, kp[tc]);
            }
#pragma unroll
            for (int t = 0; t < 10; t++) vp[t] = movm(vp[t]);
#pragma unroll
            for (int h = 0; h < 4; h++) {
                if (no_prev) sp[h][0] = sp[h][1] = -1e9f / 0.22360679774997896f;
                float a0 = le0 ? sl[h][0] : sp[h][0], a1 = le1 ? sl[h][1] : sp[h][1];
                float b0 = le0 ? sh[h][2] : sl[h][2], b1 = le1 ? sh[h][3] : sl[h][3];
                float ma = fmaxf(a0, a1), mb = fmaxf(b0, b1);
                ma = fmaxf(ma, __shfl_xor_sync(0xffffffffu, ma, 1));
                mb = fmaxf(mb, __shfl_xor_sync(0xffffffffu, mb, 1));
                ma = fmaxf(ma, __shfl_xor_sync(0xffffffffu, ma, 2));
                mb = fmaxf(mb, __shfl_xor_sync(0xffffffffu, mb, 2));
                ma *= -scl;
                mb *= -scl;
                a0 = ex2(fmaf(a0, scl, ma)), a1 = ex2(fmaf(a1, scl, ma));
                b0 = ex2(fmaf(b0, scl, mb)), b1 = ex2(fmaf(b1, scl, mb));
                row_sums(ma, mb, a0, a1, b0, b1);
                ma = rcp(ma) * g0;
                mb = rcp(mb) * g1;
                pl[h] = pack2(a0 * ma, a1 * ma);
                ph[h] = pack2(b0 * mb, b1 * mb);
            }
            uint32_t* const po = reinterpret_cast<uint32_t*>(sc + SC_O + warp * 160) + lane;
#pragma unroll
            for (int hp = 0; hp < 2; hp++) {
                float o[6][4];
#pragma unroll
                for (int h = 0; h < 2; h++) {
                    const int ta = hp * 5 + h * 3, tc = hp * 5 + 2;
                    const uint32_t a0 = pl[hp * 2 + h] & mle, a1 = ph[hp * 2 + h] & ~mle, a3 = ph[hp * 2 + h] & mle, ap = pl[hp * 2 + h] & ~mle;
#pragma unroll
                    for (int i = 0; i < 3; i++) o[h * 3 + i][0] = o[h * 3 + i][1] = o[h * 3 + i][2] = o[h * 3 + i][3] = 0.f;
#pragma unroll
                    for (int i = 0; i < 3; i++) mma8(o[h * 3 + i], a0, a1, vl[i < 2 ? ta + i : tc]);
#pragma unroll
                    for (int i = 0; i < 3; i++) mma16(o[h * 3 + i], ap, 0u, 0u, a3, vp[i < 2 ? ta + i : tc], vh[i < 2 ? ta + i : tc]);
                }
#pragma unroll
                for (int i = 0; i < 2; i++) {
                    ol[hp * 5 + i] = pack2(o[i][0], o[i][1]);
                    oh[hp * 5 + i] = pack2(o[i][2], o[i][3]);
                    ol[hp * 5 + 3 + i] = pack2(o[3 + i][0], o[3 + i][1]);
                    oh[hp * 5 + 3 + i] = pack2(o[3 + i][2], o[3 + i][3]);
                }
                ol[hp * 5 + 2] = pack2(low ? o[2][0] : o[5][0], low ? o[2][1] : o[5][1]);
                oh[hp * 5 + 2] = pack2(low ? o[2][2] : o[5][2], low ? o[2][3] : o[5][3]);
#pragma unroll
                for (int t = hp * 5; t < hp * 5 + 5; t++) {
                    st_relaxed4(po + t * 32, ol[t]);
                    st_relaxed4(po + t * 32 + 320, oh[t]);
                    if (t == 5) {
                        if (wg != HALF(hg)) bar_arrive(2, 256);
                        bar_arrive(14, 384);
                        if (lane == 0) mbar_arrive(B_HF);
                    }
                }
                if (!hp) cl = clock();
            }
        }
        TSM(warp == 0 ? 5 : warp == 4 ? 21 : warp == 5 ? 30 : warp == 1 ? 31 : warp == 2 ? 32 : warp == 3 ? 33 : warp == 6 ? 34 : 24);
        const uint4* ow = sc + (SC_O + HALF(hg) * 640 - hg * SC_SIZE);
        auto stage = [&]() {
            mbar_wait(B_INIT, 0);
            mbar_wait(B_OE, 0);
            const unsigned t0 = clock();
            uint32_t ph = 0;
#pragma unroll 1
            for (int i = w4 + 1 + NRS; i < 8; i += 4) {
                const uint4* src = ow + src_of(i, hg) * SC_SIZE;
                const uint32_t buf = o_buf(i), chk = buf + lane * 132;
                if (i >= 6) mbar_wait(B_DD, 0);
                pace(t0, (i - 3) * O_DT + O_D);
                uint32_t c;
                do {
                    if (elect_one()) {
                        mbar_expect_tx(B_OT + w4 * 8, 10240);
                        bulk_load(buf, src, 10240, B_OT + w4 * 8);
                    }
                    mbar_wait(B_OT + w4 * 8, ph);
                    if (i == 1 + NRS && !ph) TS(wg ? 19 : 20);
                    ph ^= 1;
                    c = max(max(lds4(chk), lds4(chk + 4096)), lds4(chk + 6144));
                } while (__any_sync(0xffffffffu, c == SENT));
                if (lane == 0) mbar_arrive(B_G2 + i * 8);
                TSM(32 + i);
            }
        };
        const bool idle = wg != HALF(hg);

        float oc[80];
        uint32_t routed = ~0u, n0, n1, stg, m128 = SM_SENT + lane * 16, m64 = m128, l128 = m128, l64 = m128, oa128, oa64;
        int orow;
        char *o128, *o64;
        bool nan;
        uint32_t c3 = 0;
        if (!idle || w4 == 3) {
        if (!idle) {
        uint32_t af[2][20];
        const uint32_t* const ap = reinterpret_cast<const uint32_t*>(ow + (~hg & 4) * SC_SIZE + w4 * 160) + lane;
        auto fetch = [&](int i) {
#pragma unroll
            for (int t = 0; t < 20; t++) af[i & 1][(t >> 1) + (t & 1) * 10] = ld_relaxed4(ap + i * SC_SIZE * 4 + ((t >> 1) + (t & 1) * 10) * 32);
        };
        auto missing = [&](int i, uint32_t c) {
            uint32_t m[3] = {af[i][0], af[i][1], ((uint32_t)clock() | c) >> 1};
#pragma unroll
            for (int t = 2; t < 20; t++) m[t / 2 % 3] = max(m[t / 2 % 3], af[i][t]);
            return __any_sync(0xffffffffu, max(max(m[0], m[1]), m[2]) == SENT);
        };
        auto addresses = [&](uint4 kv, uint32_t c2) {
            const uint32_t ln = lane + kv.z;
            orow = p0 + wg * 64 + w4 * 16;
            const uint32_t otok = orow * 2 + par, d1 = (~kv.x & 2047) - otok, d2 = (~kv.y & 2047) - otok;
            routed = (shl(~d1 & 1, d1 >> 1) | shl(~d2 & 1, d2 >> 1) | c2 << 16) & 0x7FFFFFFFu;
            n0 = routed >> r & 1 ? 0 : pack2(1.f - g0, 1.f - g0), n1 = routed >> r & 256 ? 0 : pack2(1.f - g1, 1.f - g1);
            stg = SM_OUT + w4 * 5120;
            m128 = stg + (ln & 15) * 128 + (((ln >> 4) ^ (ln & 7)) << 4);
            m64 = stg + 4096 + (ln & 15) * 64 + (((ln >> 4) ^ ((ln >> 1) & 3)) << 4);
            l128 = stg + (ln ^ (ln >> 3)) * 16;
            l64 = l128 + 4096;
            oa128 = otok * 1280 + kba * 128 + (ln >> 3) * (2560 - 128) + ln * 16;
            oa64 = otok * 1280 + kbr * 128 + odd * 64 + (ln >> 2) * (2560 - 64) + ln * 16;
            asm volatile("" : "+r"(n0), "+r"(n1), "+r"(routed), "+r"(m128), "+r"(m64), "+r"(l128), "+r"(oa128), "+r"(oa64));
            l64 = l128 + 4096;
        };
        auto step = [&](int i, int s) {
            wgmma_reg(oc, af[i][2 * s], af[i][10 + 2 * s], af[i][2 * s + 1], af[i][11 + 2 * s], desc_lo(wo_buf(i + 1), 10240) + s * 128, 1);
        };
        bar_sync(2, 256);
        mbar_wait(B_G2, 0);
        TSM(w4 == 0 ? 6 : 63);
        wg_fence();
#pragma unroll
        for (int s = 0; s < 5; s++)
            wgmma_reg(oc, ol[2 * s], oh[2 * s], ol[2 * s + 1], oh[2 * s + 1], desc_lo(wo_buf(0), 10240) + s * 128, s);
        wg_commit();
        mbar_wait(B_XS, 0);
        mbar_wait(B_INIT, 0);
        TSM(40 + w4);
        int nit = 0;
        const uint4 kv = lds16(SM_KEY + 64);
        fetch(0);
        uint32_t c1 = clock() | cl;
        wg_wait<0>();
        if (leader) mbar_arrive(B_OE);
        fetch(1);
        addresses(kv, clock());
        nit++;
        if (__builtin_expect(missing(0, c1), 0)) do {
            fetch(0);
            c1 = clock();
            fetch(1);
            nit++;
        } while (missing(0, c1));
        TSM(44 + w4);
        mbar_wait(B_G2 + 8, 0);
        TSM(w4 == 0 ? 7 : 63);
        wg_fence();
#pragma unroll
        for (int s = 0; s < 4; s++) step(0, s);
        const bool again = missing(1, 0);
        c1 = clock();
        step(0, 4);
        wg_commit();
        if (__builtin_expect(again, 0)) do fetch(1); while (missing(1, 0));
        TSM(56 + w4);
        mbar_wait(B_G2 + 16, 0);
        TSM(w4 == 0 ? 11 : 63);
        wg_fence();
#pragma unroll
        for (int s = 0; s < 5; s++) step(1, s);
        wg_commit();
        c3 = c1;
        wg_wait<1>();
        if (leader) mbar_arrive(B_OE + 8);
#pragma unroll 1
        for (int i = 3; i < 8; i++) {
            const uint32_t ao = desc_lo(0, 128) + (o_buf(i) >> 4), wo = desc_lo(0, 10240) + (wo_buf(i) >> 4);
            mbar_wait(B_G2 + i * 8, 0);
            TSM(w4 == 0 ? (i < 7 ? 9 + i : 17) : 63);
            wg_fence();
#pragma unroll
            for (int s = 0; s < 5; s++) wgmma_out64(oc, ao + s * 16, wo + s * 128, 1);
            wg_commit();
#pragma unroll
            for (int s = 0; s < 5; s++) wgmma_out96(oc, ao + s * 16, wo + 640 + s * 128, 1);
            wg_commit();
            if (i == 3) {
                wg_wait<2>();
                if (leader) mbar_arrive(B_OE + 16);
            }
        }
        o128 = reinterpret_cast<char*>(P.op) + oa128;
        o64 = reinterpret_cast<char*>(P.op) + oa64;
        TS(w4 == 0 ? 8 : 63);

        wg_wait<1>();
        TSM(w4 == 0 ? 9 : 63);
        }
        const bool rt0 = routed >> r & 1, rt1 = routed >> r & 256;
#pragma unroll
        for (int pi = 0; pi < 3; pi++) {
            const int part = pi < 2 ? 1 - pi : pi;
            if (pi == 1) {
                c3 |= clock();
                wg_wait<0>();
            }
            const int s0 = part ? part * 4 - 4 : 8, ns = part ? 4 : 2;
#pragma unroll
            for (int i = 0; i < 4; i++) {
                if (i >= ns) break;
                const int s = s0 + i;
                const uint32_t y0 = hfma2(n0, nb[s * 4], pack2(oc[s * 8 + 0], oc[s * 8 + 1]));
                const uint32_t y1 = hfma2(n1, nb[s * 4 + 1], pack2(oc[s * 8 + 2], oc[s * 8 + 3]));
                const uint32_t y2 = hfma2(n0, nb[s * 4 + 2], pack2(oc[s * 8 + 4], oc[s * 8 + 5]));
                const uint32_t y3 = hfma2(n1, nb[s * 4 + 3], pack2(oc[s * 8 + 6], oc[s * 8 + 7]));
                if (s == 0) nan = u2f(y0) != u2f(y0) || u2f(y1) != u2f(y1);
                stsm(((s < 8 ? m128 : m64) ^ ((s & 3) * 32)) + (s & 4) * 512, y0, y1, y2, y3);
            }
            __syncwarp();
            if (pi == 2 && lane == 0 && (int)routed >= 0) mbar_arrive(B_DONE);
            uint4 v[4];
#pragma unroll
            for (int i = 0; i < 4; i++)
                if (i < ns) v[i] = lds16(!part ? l64 + i * 512 : (l128 ^ ((i & 1) * 64)) + i * 512 + s0 * 512);
#pragma unroll
            for (int i = 0; i < 4; i++)
                if (i < ns && !(part ? routed >> (lane >> 3) & 1 << 4 * i : i ? rt1 : rt0))
                    *reinterpret_cast<uint4*>(!part ? o64 + i * 8 * 2560 : o128 + i * 4 * 2560 + s0 * 32) = v[i];
            if (pi == 0) TS(w4 == 0 ? 1 : 63);
        }
        TSM(w4 == 0 ? 10 : idle ? 62 : 63);
        }
        if (idle) {
            stage();
            return;
        }
        const bool rt0 = routed >> r & 1, rt1 = routed >> r & 256;
        uint32_t redo;
        asm volatile("{\n.reg .pred p, q;\nsetp.eq.u32 p, %1, 0xFFFFFFFF;\nbar.cta.red.or.pred q, 10, 128, p;\nselp.u32 %0, 1, 0, q;\n}"
                     : "=r"(redo) : "r"(nan ? SENT : c3 >> 1) : "memory");
        if (redo) {
            const int cb = CB(hg);
#pragma unroll 1
            for (int i = 0; i < 8; i++) {
                if (leader) {
                    mbar_expect_tx(B_RE, 25600);
                    tma_3d(SM_W, &P.woa, B_RE, 0, i * 80, (cb * 5 + 1) >> 1);
                    tma_2d(SM_W + 20480, &P.wob, B_RE, cb * 160 + ((cb & 1) ? 0 : 128), i * 80);
                }
#pragma unroll 1
                for (int s = 0; s < 20; s++) {
                    const int w = w4 * 640 + s * 32 + lane;
                    uint32_t v, it = 0;
                    do {
                        v = ld_relaxed4(reinterpret_cast<const uint32_t*>(ow + i * SC_SIZE) + w);
                        if (++it > (1u << 22)) fault();
                    } while ((v >> 16) == 0xFFFFu || (v & 0xFFFFu) == 0xFFFFu);
                    sts4(SM_X + w * 4, v);
                }
                fence_async_smem();
                __syncwarp();
                bar_sync(10, 128);
                mbar_wait(B_RE, i & 1);
                wg_fence();
#pragma unroll
                for (int s = 0; s < 5; s++) {
                    wgmma_out64(oc, desc_lo(SM_X, 128) + s * 16, desc_lo(SM_W, 10240) + s * 128, s || i);
                    wgmma_out96(oc, desc_lo(SM_X, 128) + s * 16, desc_lo(SM_W, 10240) + 640 + s * 128, s || i);
                }
                wg_commit();
                wg_wait<0>();
                bar_sync(10, 128);
            }
#pragma unroll
            for (int t = 0; t < 40; t++) {
                const int col = (t < 32 ? kba * 64 + (t >> 1) * 8 : kbr * 64 + odd * 32 + ((t - 32) >> 1) * 8) + cq * 2;
                const uint32_t y = hfma2((t & 1) ? n1 : n0, nb[t], pack2(oc[2 * t], oc[2 * t + 1]));
                sts4(stg + cq * 4 + (t < 32 ? (t >> 4) * 2048 + (r + (t & 1) * 8) * 128 + ((((t >> 1) & 7) ^ r) << 4)
                                            : 4096 + (r + (t & 1) * 8) * 64 + ((((t - 32) >> 1) ^ (r >> 1)) << 4)), y);
                if (!((t & 1) ? rt1 : rt0)) *reinterpret_cast<uint32_t*>(P.op + ((orow + r + (t & 1) * 8) * 2 + par) * 640 + col) = y;
            }
            bar_sync(10, 128);
            if (leader) mbar_arrive(B_OE + 24);
        }
    }
}

typedef CUresult (*EncodeFn)(CUtensorMap*, CUtensorMapDataType, cuuint32_t, void*, const cuuint64_t*, const cuuint64_t*,
                             const cuuint32_t*, const cuuint32_t*, CUtensorMapInterleave, CUtensorMapSwizzle,
                             CUtensorMapL2promotion, CUtensorMapFloatOOBfill);

void encode(EncodeFn fn, CUtensorMap* m, const void* ptr, int rank, const cuuint64_t* dims, const cuuint64_t* strides,
            const cuuint32_t* box, CUtensorMapSwizzle swz,
            CUtensorMapL2promotion promo = CU_TENSOR_MAP_L2_PROMOTION_L2_128B) {
    const cuuint32_t es[4] = {1, 1, 1, 1};
    fn(m, CU_TENSOR_MAP_DATA_TYPE_BFLOAT16, rank, const_cast<void*>(ptr), dims, strides, box, es,
       CU_TENSOR_MAP_INTERLEAVE_NONE, swz, promo, CU_TENSOR_MAP_FLOAT_OOB_FILL_NONE);
}

}

extern "C" void kernel_launch(void* const* d_in, const int* in_sizes, int n_in, void* d_out, int out_size) {
    (void)in_sizes; (void)n_in; (void)out_size;
    Params P;
    P.xp = (const __nv_bfloat16*)d_in[0];
    P.upp = (const __nv_bfloat16*)d_in[6];
    P.op = (__nv_bfloat16*)d_out;
    P.w_r = (const __nv_bfloat16*)d_in[4];
    P.gate_w = (const __nv_bfloat16*)d_in[8];

    void* fp = nullptr;
    cudaDriverEntryPointQueryResult st;
    cudaGetDriverEntryPoint("cuTensorMapEncodeTiled", &fp, cudaEnableDefault, &st);
    EncodeFn fn = (EncodeFn)fp;
    const cuuint64_t xd[3] = {640, 2, 1024}, xs[2] = {1280, 2560};
    const cuuint32_t bx[3] = {64, 1, 64}, bx2[3] = {64, 1, 128};
    encode(fn, &P.x2, d_in[0], 3, xd, xs, bx2, CU_TENSOR_MAP_SWIZZLE_128B);
    encode(fn, &P.x, d_in[0], 3, xd, xs, bx, CU_TENSOR_MAP_SWIZZLE_128B);
    const cuuint64_t wd[3] = {640, 640, 3}, ws[2] = {3840, 1280};
    const cuuint32_t bw[3] = {64, 32, 3}, bwr[3] = {16, 32, 3};
    encode(fn, &P.w, d_in[1], 3, wd, ws, bw, CU_TENSOR_MAP_SWIZZLE_128B);
    encode(fn, &P.wr, d_in[1], 3, wd, ws, bwr, CU_TENSOR_MAP_SWIZZLE_32B);
    const cuuint64_t ad[3] = {64, 640, 10}, as[2] = {1280, 128}, bd[2] = {640, 640};
    const cuuint32_t ba[3] = {64, 80, 2}, bb[2] = {32, 80};
    encode(fn, &P.woa, d_in[2], 3, ad, as, ba, CU_TENSOR_MAP_SWIZZLE_128B, CU_TENSOR_MAP_L2_PROMOTION_NONE);
    encode(fn, &P.wob, d_in[2], 2, bd, as, bb, CU_TENSOR_MAP_SWIZZLE_128B, CU_TENSOR_MAP_L2_PROMOTION_NONE);
    const cuuint64_t gd[2] = {1728, 640}, gs[1] = {3456}, dd[3] = {64, 1728, 10};
    const cuuint32_t bg[2] = {64, 32}, bu[2] = {64, 48}, bdn[3] = {64, 64, 1}, bxg[3] = {64, 1, 16};
    encode(fn, &P.xg, d_in[0], 3, xd, xs, bxg, CU_TENSOR_MAP_SWIZZLE_128B);
    encode(fn, &P.gate, d_in[5], 2, gd, gs, bg, CU_TENSOR_MAP_SWIZZLE_128B);
    encode(fn, &P.up, d_in[6], 2, gd, gs, bg, CU_TENSOR_MAP_SWIZZLE_128B);
    encode(fn, &P.up2, d_in[6], 2, gd, gs, bu, CU_TENSOR_MAP_SWIZZLE_128B);
    encode(fn, &P.down, d_in[7], 3, dd, as, bdn, CU_TENSOR_MAP_SWIZZLE_128B);

    cudaFuncSetAttribute(fused_kernel, cudaFuncAttributeMaxDynamicSharedMemorySize, SM_TOTAL);
    fused_kernel<<<NCTA, 512, SM_TOTAL, cudaStreamPerThread>>>(P);
}
```

```cpp
#include <cuda_runtime.h>
#include <cuda_bf16.h>
#include <cuda.h>
#include <stdint.h>

namespace {

constexpr int NCTA = 128;
constexpr int NFFN = 108;
constexpr uint32_t SENT = 0xFFFFFFFFu;

constexpr uint32_t SB = 1024;
constexpr uint32_t SM_W = SB;
constexpr uint32_t SM_X = SB + 122880;
constexpr uint32_t SM_F = SB + 188416;
constexpr uint32_t SM_G = SB + 212992;
constexpr uint32_t SM_BAR = SB + 223232;
constexpr uint32_t SM_PROF = SB + 223744;
constexpr uint32_t SM_KEY = SB + 224000;
constexpr uint32_t SM_RED = SB + 224128;
constexpr uint32_t SM_XS = SB + 226688;
constexpr uint32_t SM_SENT = SB + 227328;
constexpr uint32_t SM_U = SM_RED + 1920;
constexpr uint32_t SM_GATE = SM_RED;
constexpr uint32_t SM_TOTAL = 232448;
constexpr uint32_t SM_HALO1 = SM_X + 30720;
constexpr uint32_t SM_HALO = SM_HALO1 + 12800;
constexpr uint32_t SM_UP = SM_W + 61440;
constexpr uint32_t SM_DN = SM_UP + 6144;
constexpr uint32_t SM_Y = SM_F + 26624;
constexpr uint32_t SM_OUT = SM_W + 92160;

constexpr uint32_t B_XL0 = SM_BAR, B_FULL = SM_BAR + 8, B_GT = SM_BAR + 72, B_RG = SM_BAR + 80, B_RG2 = SM_BAR + 88,
                   B_XS = SM_BAR + 96, B_EMPTY = SM_BAR + 128, B_DONE = SM_BAR + 192, B_XE = SM_BAR + 200,
                   B_GUD = SM_BAR + 224, B_OE = B_GUD + 8, B_OT = B_GUD + 40, B_MOD = B_GUD + 72,
                   B_GU = SM_BAR + 104, B_ALL = SM_BAR + 112, B_UP = SM_BAR + 120, B_DN = B_GUD + 80, B_RS = B_GUD + 88, B_INIT = B_GUD + 96,
                   B_RE = B_GUD + 104, B_G2 = B_GUD + 112, B_DD = B_GUD + 176, B_HF = B_GUD + 184;

struct Params {
    CUtensorMap x, x2, w, wr, woa, wob, xg, gate, up, up2, down;
    __nv_bfloat16* op;
    const __nv_bfloat16 *xp, *upp, *w_r, *gate_w;
    uint32_t src[8];
};

constexpr int SC_O = 0;
constexpr int SC_HALO = 1280;
constexpr int SC_GU = 1440;
constexpr int SC_Y = 1504;
constexpr int SC_SIZE = 1600;
__device__ __align__(128) uint4 g_sc[NCTA * SC_SIZE];
__device__ __align__(128) uint4 g_cand[NCTA];
__device__ __align__(16) uint32_t g_gate[2048];
__device__ __align__(128) unsigned g_cnt[64];
#define TSM(i) do { } while (0)
#define TS(i) do { } while (0)
#define TS2(i) do { } while (0)
#define TSX(i) do { } while (0)

__device__ __forceinline__ uint32_t smem_u32(const void* p) { return (uint32_t)__cvta_generic_to_shared(p); }
__device__ __forceinline__ void fault() { asm volatile("st.shared.u32 [%0], %0;" ::"r"(0x100001) : "memory"); }
__device__ __forceinline__ void mbar_init(uint32_t bar, uint32_t cnt) {
    asm volatile("mbarrier.init.shared::cta.b64 [%0], %1;" ::"r"(bar), "r"(cnt) : "memory");
}
__device__ __forceinline__ void mbar_expect_tx(uint32_t bar, uint32_t bytes) {
    asm volatile("mbarrier.arrive.expect_tx.shared::cta.b64 _, [%0], %1;" ::"r"(bar), "r"(bytes) : "memory");
}
__device__ __forceinline__ void mbar_arrive(uint32_t bar) {
    asm volatile("mbarrier.arrive.shared::cta.b64 _, [%0];" ::"r"(bar) : "memory");
}
__device__ __forceinline__ bool mbar_try(uint32_t bar, uint32_t parity) {
    uint32_t ok;
    asm volatile("{\n.reg .pred p;\nmbarrier.try_wait.parity.shared::cta.b64 p, [%1], %2;\nselp.u32 %0, 1, 0, p;\n}"
                 : "=r"(ok) : "r"(bar), "r"(parity) : "memory");
    return ok;
}
__device__ __forceinline__ void mbar_wait(uint32_t bar, uint32_t parity) {
    asm volatile("{\n.reg .pred p;\nAGAIN:\nmbarrier.try_wait.parity.shared::cta.b64 p, [%0], %1;\n@!p bra AGAIN;\n}"
                 ::"r"(bar), "r"(parity) : "memory");
}
__device__ __forceinline__ void tma_2d(uint32_t dst, const CUtensorMap* m, uint32_t bar, int c0, int c1) {
    asm volatile("cp.async.bulk.tensor.2d.shared::cluster.global.mbarrier::complete_tx::bytes [%0], [%1, {%3, %4}], [%2];"
                 ::"r"(dst), "l"(m), "r"(bar), "r"(c0), "r"(c1) : "memory");
}
__device__ __forceinline__ void bulk_load(uint32_t dst, const void* src, uint32_t bytes, uint32_t bar) {
    asm volatile("cp.async.bulk.shared::cluster.global.mbarrier::complete_tx::bytes [%0], [%1], %2, [%3];"
                 ::"r"(dst), "l"(src), "r"(bytes), "r"(bar) : "memory");
}
__device__ __forceinline__ void bulk_store(void* dst, uint32_t src, uint32_t bytes) {
    asm volatile("cp.async.bulk.global.shared::cta.bulk_group [%0], [%1], %2;" ::"l"(dst), "r"(src), "r"(bytes) : "memory");
}
__device__ __forceinline__ void tma_3d(uint32_t dst, const CUtensorMap* m, uint32_t bar, int c0, int c1, int c2) {
    asm volatile("cp.async.bulk.tensor.3d.shared::cluster.global.mbarrier::complete_tx::bytes [%0], [%1, {%3, %4, %5}], [%2];"
                 ::"r"(dst), "l"(m), "r"(bar), "r"(c0), "r"(c1), "r"(c2) : "memory");
}
__device__ __forceinline__ void fence_async_smem() { asm volatile("fence.proxy.async.shared::cta;" ::: "memory"); }
__device__ __forceinline__ void wg_fence() { asm volatile("wgmma.fence.sync.aligned;" ::: "memory"); }
__device__ __forceinline__ void wg_commit() { asm volatile("wgmma.commit_group.sync.aligned;" ::: "memory"); }
template <int N> __device__ __forceinline__ void wg_wait() { asm volatile("wgmma.wait_group.sync.aligned %0;" ::"n"(N) : "memory"); }
__device__ __forceinline__ void bar_sync(int id, int n) { asm volatile("bar.cta.sync %0, %1;" ::"r"(id), "r"(n) : "memory"); }
__device__ __forceinline__ void bar_arrive(int id, int n) { asm volatile("bar.cta.arrive %0, %1;" ::"r"(id), "r"(n) : "memory"); }

__device__ constexpr uint32_t desc_lo(uint32_t addr, uint32_t lbo) { return (addr >> 4) | ((lbo >> 4) << 16); }
__device__ __forceinline__ bool elect_one() {
    uint32_t p;
    asm volatile("{\n.reg .pred p;\nelect.sync _|p, 0xffffffff;\nselp.u32 %0, 1, 0, p;\n}" : "=r"(p));
    return p;
}
__device__ __forceinline__ uint32_t ld_relaxed4(const void* p) {
    uint32_t v;
    asm volatile("ld.relaxed.gpu.global.u32 %0, [%1];" : "=r"(v) : "l"(p) : "memory");
    return v;
}
__device__ __forceinline__ void st_relaxed4(void* p, uint32_t v) {
    asm volatile("st.relaxed.gpu.global.u32 [%0], %1;" ::"l"(p), "r"(v) : "memory");
}
__device__ __forceinline__ void red_inc(unsigned* p, unsigned after) {
    asm volatile("red.relaxed.gpu.global.add.u32 [%0], 1;" ::"l"(p), "r"(after) : "memory");
}
__device__ __forceinline__ uint32_t lds4(uint32_t a) {
    uint32_t v;
    asm volatile("ld.shared.u32 %0, [%1];" : "=r"(v) : "r"(a) : "memory");
    return v;
}
__device__ __forceinline__ void sts4(uint32_t a, uint32_t v) { asm volatile("st.shared.u32 [%0], %1;" ::"r"(a), "r"(v) : "memory"); }
__device__ __forceinline__ uint32_t hadd2(uint32_t a, uint32_t b) {
    uint32_t d;
    asm("add.rn.bf16x2 %0, %1, %2;" : "=r"(d) : "r"(a), "r"(b));
    return d;
}
__device__ __forceinline__ uint32_t hfma2(uint32_t a, uint32_t b, uint32_t c) {
    uint32_t d;
    asm("fma.rn.bf16x2 %0, %1, %2, %3;" : "=r"(d) : "r"(a), "r"(b), "r"(c));
    return d;
}
__device__ __forceinline__ uint4 ld_relaxed16(const void* p) {
    uint4 v;
    asm volatile("{\n.reg .b128 t;\n.reg .b64 lo, hi;\nld.relaxed.gpu.global.b128 t, [%4];\nmov.b128 {lo, hi}, t;\n"
                 "mov.b64 {%0, %1}, lo;\nmov.b64 {%2, %3}, hi;\n}" : "=r"(v.x), "=r"(v.y), "=r"(v.z), "=r"(v.w) : "l"(p) : "memory");
    return v;
}
__device__ __forceinline__ void st_relaxed16(void* p, uint32_t a, uint32_t b, uint32_t c, uint32_t d) {
    uint64_t lo = (uint64_t)a | ((uint64_t)b << 32), hi = (uint64_t)c | ((uint64_t)d << 32);
    asm volatile("{\n.reg .b128 t;\nmov.b128 t, {%1, %2};\nst.relaxed.gpu.global.b128 [%0], t;\n}" ::"l"(p), "l"(lo), "l"(hi) : "memory");
}
__device__ __forceinline__ uint4 lds16(uint32_t a) {
    uint4 v;
    asm volatile("ld.shared.v4.u32 {%0, %1, %2, %3}, [%4];" : "=r"(v.x), "=r"(v.y), "=r"(v.z), "=r"(v.w) : "r"(a) : "memory");
    return v;
}
__device__ __forceinline__ void sts16(uint32_t a, uint32_t x, uint32_t y, uint32_t z, uint32_t w) {
    asm volatile("st.shared.v4.u32 [%0], {%1, %2, %3, %4};" ::"r"(a), "r"(x), "r"(y), "r"(z), "r"(w) : "memory");
}
__device__ __forceinline__ uint32_t pack2(float lo, float hi) {
    uint32_t r;
    asm("cvt.rn.bf16x2.f32 %0, %1, %2;" : "=r"(r) : "f"(hi), "f"(lo));
    return r;
}
__device__ __forceinline__ uint32_t pack2v(float lo, float hi) {
    uint32_t r;
    asm volatile("cvt.rn.bf16x2.f32 %0, %1, %2;" : "=r"(r) : "f"(hi), "f"(lo));
    return r;
}
__device__ __forceinline__ uint32_t shl(uint32_t v, uint32_t n) {
    uint32_t r;
    asm("shl.b32 %0, %1, %2;" : "=r"(r) : "r"(v), "r"(n));
    return r;
}
__device__ __forceinline__ float bf_lo(uint32_t u) { return __uint_as_float(u << 16); }
__device__ __forceinline__ float bf_hi(uint32_t u) { return __uint_as_float(u & 0xFFFF0000u); }
__device__ __forceinline__ float bf_round(float f) { return __bfloat162float(__float2bfloat16_rn(f)); }
__device__ __forceinline__ uint32_t movm(uint32_t a) {
    uint32_t d;
    asm volatile("movmatrix.sync.aligned.m8n8.trans.b16 %0, %1;" : "=r"(d) : "r"(a));
    return d;
}
__device__ __forceinline__ void mma16(float (&c)[4], uint32_t a0, uint32_t a1, uint32_t a2, uint32_t a3, uint32_t b0, uint32_t b1) {
    asm volatile("mma.sync.aligned.m16n8k16.row.col.f32.bf16.bf16.f32 {%0,%1,%2,%3}, {%4,%5,%6,%7}, {%8,%9}, {%0,%1,%2,%3};"
                 : "+f"(c[0]), "+f"(c[1]), "+f"(c[2]), "+f"(c[3]) : "r"(a0), "r"(a1), "r"(a2), "r"(a3), "r"(b0), "r"(b1));
}
__device__ __forceinline__ void mma8(float (&c)[4], uint32_t a0, uint32_t a1, uint32_t b0) {
    asm volatile("mma.sync.aligned.m16n8k8.row.col.f32.bf16.bf16.f32 {%0,%1,%2,%3}, {%4,%5}, {%6}, {%0,%1,%2,%3};"
                 : "+f"(c[0]), "+f"(c[1]), "+f"(c[2]), "+f"(c[3]) : "r"(a0), "r"(a1), "r"(b0));
}
__device__ __forceinline__ float ex2(float x) { float y; asm("ex2.approx.ftz.f32 %0, %1;" : "=f"(y) : "f"(x)); return y; }
__device__ __forceinline__ float rcp(float x) { float y; asm("rcp.approx.ftz.f32 %0, %1;" : "=f"(y) : "f"(x)); return y; }
__device__ __forceinline__ float sigmoidf(float z) { return rcp(1.0f + ex2(z * -1.4426950408889634f)); }
__device__ __forceinline__ float u2f(uint32_t u) { return __uint_as_float(u); }
__device__ __forceinline__ uint32_t f2u(float f) { return __float_as_uint(f); }

__device__ __forceinline__ void wgmma_main(float (&d)[96], uint32_t a, uint32_t b, int scale_d) {
    asm volatile("{\n.reg .pred p;\n.reg .b64 da, db;\nsetp.ne.b32 p, %98, 0;\n"
        "mov.b64 da, {%96, 0x40000040};\nmov.b64 db, {%97, 0x40000040};\n"
        "wgmma.mma_async.sync.aligned.m64n192k16.f32.bf16.bf16 "
        "{%0, %1, %2, %3, %4, %5, %6, %7, %8, %9, %10, %11, %12, %13, %14, %15, "
        "%16, %17, %18, %19, %20, %21, %22, %23, %24, %25, %26, %27, %28, %29, %30, %31, "
        "%32, %33, %34, %35, %36, %37, %38, %39, %40, %41, %42, %43, %44, %45, %46, %47, "
        "%48, %49, %50, %51, %52, %53, %54, %55, %56, %57, %58, %59, %60, %61, %62, %63, "
        "%64, %65, %66, %67, %68, %69, %70, %71, %72, %73, %74, %75, %76, %77, %78, %79, "
        "%80, %81, %82, %83, %84, %85, %86, %87, %88, %89, %90, %91, %92, %93, %94, %95}, "
        "da, db, p, 1, 1, 0, 1;\n}\n"
        : "+f"(d[0]), "+f"(d[1]), "+f"(d[2]), "+f"(d[3]), "+f"(d[4]), "+f"(d[5]), "+f"(d[6]), "+f"(d[7]),
          "+f"(d[8]), "+f"(d[9]), "+f"(d[10]), "+f"(d[11]), "+f"(d[12]), "+f"(d[13]), "+f"(d[14]), "+f"(d[15]),
          "+f"(d[16]), "+f"(d[17]), "+f"(d[18]), "+f"(d[19]), "+f"(d[20]), "+f"(d[21]), "+f"(d[22]), "+f"(d[23]),
          "+f"(d[24]), "+f"(d[25]), "+f"(d[26]), "+f"(d[27]), "+f"(d[28]), "+f"(d[29]), "+f"(d[30]), "+f"(d[31]),
          "+f"(d[32]), "+f"(d[33]), "+f"(d[34]), "+f"(d[35]), "+f"(d[36]), "+f"(d[37]), "+f"(d[38]), "+f"(d[39]),
          "+f"(d[40]), "+f"(d[41]), "+f"(d[42]), "+f"(d[43]), "+f"(d[44]), "+f"(d[45]), "+f"(d[46]), "+f"(d[47]),
          "+f"(d[48]), "+f"(d[49]), "+f"(d[50]), "+f"(d[51]), "+f"(d[52]), "+f"(d[53]), "+f"(d[54]), "+f"(d[55]),
          "+f"(d[56]), "+f"(d[57]), "+f"(d[58]), "+f"(d[59]), "+f"(d[60]), "+f"(d[61]), "+f"(d[62]), "+f"(d[63]),
          "+f"(d[64]), "+f"(d[65]), "+f"(d[66]), "+f"(d[67]), "+f"(d[68]), "+f"(d[69]), "+f"(d[70]), "+f"(d[71]),
          "+f"(d[72]), "+f"(d[73]), "+f"(d[74]), "+f"(d[75]), "+f"(d[76]), "+f"(d[77]), "+f"(d[78]), "+f"(d[79]),
          "+f"(d[80]), "+f"(d[81]), "+f"(d[82]), "+f"(d[83]), "+f"(d[84]), "+f"(d[85]), "+f"(d[86]), "+f"(d[87]),
          "+f"(d[88]), "+f"(d[89]), "+f"(d[90]), "+f"(d[91]), "+f"(d[92]), "+f"(d[93]), "+f"(d[94]), "+f"(d[95])
        : "r"(a), "r"(b), "r"(scale_d));
}

__device__ __forceinline__ void wgmma_rem(float (&d)[24], uint32_t a, uint32_t b, int scale_d) {
    asm volatile("{\n.reg .pred p;\n.reg .b64 da, db;\nsetp.ne.b32 p, %26, 0;\n"
        "mov.b64 da, {%24, 0x40000040};\nmov.b64 db, {%25, 0xC0000010};\n"
        "wgmma.mma_async.sync.aligned.m64n48k16.f32.bf16.bf16 "
        "{%0, %1, %2, %3, %4, %5, %6, %7, %8, %9, %10, %11, %12, %13, %14, %15, "
        "%16, %17, %18, %19, %20, %21, %22, %23}, "
        "da, db, p, 1, 1, 0, 1;\n}\n"
        : "+f"(d[0]), "+f"(d[1]), "+f"(d[2]), "+f"(d[3]), "+f"(d[4]), "+f"(d[5]), "+f"(d[6]), "+f"(d[7]),
          "+f"(d[8]), "+f"(d[9]), "+f"(d[10]), "+f"(d[11]), "+f"(d[12]), "+f"(d[13]), "+f"(d[14]), "+f"(d[15]),
          "+f"(d[16]), "+f"(d[17]), "+f"(d[18]), "+f"(d[19]), "+f"(d[20]), "+f"(d[21]), "+f"(d[22]), "+f"(d[23])
        : "r"(a), "r"(b), "r"(scale_d));
}

__device__ __forceinline__ void wgmma_out64(float (&d)[80], uint32_t a, uint32_t b, int scale_d) {
    asm volatile("{\n.reg .pred p;\n.reg .b64 da, db;\nsetp.ne.b32 p, %34, 0;\n"
        "mov.b64 da, {%32, 0x50};\nmov.b64 db, {%33, 0x40000040};\n"
        "wgmma.mma_async.sync.aligned.m64n64k16.f32.bf16.bf16 "
        "{%0, %1, %2, %3, %4, %5, %6, %7, %8, %9, %10, %11, %12, %13, %14, %15, "
        "%16, %17, %18, %19, %20, %21, %22, %23, %24, %25, %26, %27, %28, %29, %30, %31}, "
        "da, db, p, 1, 1, 0, 1;\n}\n"
        : "+f"(d[0]), "+f"(d[1]), "+f"(d[2]), "+f"(d[3]), "+f"(d[4]), "+f"(d[5]), "+f"(d[6]), "+f"(d[7]),
          "+f"(d[8]), "+f"(d[9]), "+f"(d[10]), "+f"(d[11]), "+f"(d[12]), "+f"(d[13]), "+f"(d[14]), "+f"(d[15]),
          "+f"(d[16]), "+f"(d[17]), "+f"(d[18]), "+f"(d[19]), "+f"(d[20]), "+f"(d[21]), "+f"(d[22]), "+f"(d[23]),
          "+f"(d[24]), "+f"(d[25]), "+f"(d[26]), "+f"(d[27]), "+f"(d[28]), "+f"(d[29]), "+f"(d[30]), "+f"(d[31])
        : "r"(a), "r"(b), "r"(scale_d));
}
__device__ __forceinline__ void wgmma_out96(float (&d)[80], uint32_t a, uint32_t b, int scale_d) {
    asm volatile("{\n.reg .pred p;\n.reg .b64 da, db;\nsetp.ne.b32 p, %50, 0;\n"
        "mov.b64 da, {%48, 0x50};\nmov.b64 db, {%49, 0x40000040};\n"
        "wgmma.mma_async.sync.aligned.m64n96k16.f32.bf16.bf16 "
        "{%0, %1, %2, %3, %4, %5, %6, %7, %8, %9, %10, %11, %12, %13, %14, %15, "
        "%16, %17, %18, %19, %20, %21, %22, %23, %24, %25, %26, %27, %28, %29, %30, %31, "
        "%32, %33, %34, %35, %36, %37, %38, %39, %40, %41, %42, %43, %44, %45, %46, %47}, "
        "da, db, p, 1, 1, 0, 1;\n}\n"
        : "+f"(d[32]), "+f"(d[33]), "+f"(d[34]), "+f"(d[35]), "+f"(d[36]), "+f"(d[37]), "+f"(d[38]), "+f"(d[39]),
          "+f"(d[40]), "+f"(d[41]), "+f"(d[42]), "+f"(d[43]), "+f"(d[44]), "+f"(d[45]), "+f"(d[46]), "+f"(d[47]),
          "+f"(d[48]), "+f"(d[49]), "+f"(d[50]), "+f"(d[51]), "+f"(d[52]), "+f"(d[53]), "+f"(d[54]), "+f"(d[55]),
          "+f"(d[56]), "+f"(d[57]), "+f"(d[58]), "+f"(d[59]), "+f"(d[60]), "+f"(d[61]), "+f"(d[62]), "+f"(d[63]),
          "+f"(d[64]), "+f"(d[65]), "+f"(d[66]), "+f"(d[67]), "+f"(d[68]), "+f"(d[69]), "+f"(d[70]), "+f"(d[71]),
          "+f"(d[72]), "+f"(d[73]), "+f"(d[74]), "+f"(d[75]), "+f"(d[76]), "+f"(d[77]), "+f"(d[78]), "+f"(d[79])
        : "r"(a), "r"(b), "r"(scale_d));
}
__device__ __forceinline__ void wgmma_reg64(float (&d)[80], uint32_t a0, uint32_t a1, uint32_t a2, uint32_t a3, uint32_t b, int scale_d) {
    asm volatile("{\n.reg .pred p;\n.reg .b64 db;\nsetp.ne.b32 p, %37, 0;\nmov.b64 db, {%36, 0x40000040};\n"
        "wgmma.mma_async.sync.aligned.m64n64k16.f32.bf16.bf16 "
        "{%0, %1, %2, %3, %4, %5, %6, %7, %8, %9, %10, %11, %12, %13, %14, %15, "
        "%16, %17, %18, %19, %20, %21, %22, %23, %24, %25, %26, %27, %28, %29, %30, %31}, "
        "{%32, %33, %34, %35}, db, p, 1, 1, 1;\n}\n"
        : "+f"(d[0]), "+f"(d[1]), "+f"(d[2]), "+f"(d[3]), "+f"(d[4]), "+f"(d[5]), "+f"(d[6]), "+f"(d[7]),
          "+f"(d[8]), "+f"(d[9]), "+f"(d[10]), "+f"(d[11]), "+f"(d[12]), "+f"(d[13]), "+f"(d[14]), "+f"(d[15]),
          "+f"(d[16]), "+f"(d[17]), "+f"(d[18]), "+f"(d[19]), "+f"(d[20]), "+f"(d[21]), "+f"(d[22]), "+f"(d[23]),
          "+f"(d[24]), "+f"(d[25]), "+f"(d[26]), "+f"(d[27]), "+f"(d[28]), "+f"(d[29]), "+f"(d[30]), "+f"(d[31])
        : "r"(a0), "r"(a1), "r"(a2), "r"(a3), "r"(b), "r"(scale_d));
}
__device__ __forceinline__ void wgmma_reg96(float (&d)[80], uint32_t a0, uint32_t a1, uint32_t a2, uint32_t a3, uint32_t b, int scale_d) {
    asm volatile("{\n.reg .pred p;\n.reg .b64 db;\nsetp.ne.b32 p, %53, 0;\nmov.b64 db, {%52, 0x40000040};\n"
        "wgmma.mma_async.sync.aligned.m64n96k16.f32.bf16.bf16 "
        "{%0, %1, %2, %3, %4, %5, %6, %7, %8, %9, %10, %11, %12, %13, %14, %15, "
        "%16, %17, %18, %19, %20, %21, %22, %23, %24, %25, %26, %27, %28, %29, %30, %31, "
        "%32, %33, %34, %35, %36, %37, %38, %39, %40, %41, %42, %43, %44, %45, %46, %47}, "
        "{%48, %49, %50, %51}, db, p, 1, 1, 1;\n}\n"
        : "+f"(d[32]), "+f"(d[33]), "+f"(d[34]), "+f"(d[35]), "+f"(d[36]), "+f"(d[37]), "+f"(d[38]), "+f"(d[39]),
          "+f"(d[40]), "+f"(d[41]), "+f"(d[42]), "+f"(d[43]), "+f"(d[44]), "+f"(d[45]), "+f"(d[46]), "+f"(d[47]),
          "+f"(d[48]), "+f"(d[49]), "+f"(d[50]), "+f"(d[51]), "+f"(d[52]), "+f"(d[53]), "+f"(d[54]), "+f"(d[55]),
          "+f"(d[56]), "+f"(d[57]), "+f"(d[58]), "+f"(d[59]), "+f"(d[60]), "+f"(d[61]), "+f"(d[62]), "+f"(d[63]),
          "+f"(d[64]), "+f"(d[65]), "+f"(d[66]), "+f"(d[67]), "+f"(d[68]), "+f"(d[69]), "+f"(d[70]), "+f"(d[71]),
          "+f"(d[72]), "+f"(d[73]), "+f"(d[74]), "+f"(d[75]), "+f"(d[76]), "+f"(d[77]), "+f"(d[78]), "+f"(d[79])
        : "r"(a0), "r"(a1), "r"(a2), "r"(a3), "r"(b), "r"(scale_d));
}
__device__ __forceinline__ void wgmma_reg(float (&d)[80], uint32_t a0, uint32_t a1, uint32_t a2, uint32_t a3, uint32_t b, int scale_d) {
    wgmma_reg64(d, a0, a1, a2, a3, b, scale_d);
    wgmma_reg96(d, a0, a1, a2, a3, b + 640, scale_d);
}
#define TSQ(i) do { } while (0)
#define TSR(i) do { } while (0)
#define MAP_TILE(b) (((b) & 1) | (((b) >> 1) & 2) | (((b) >> 5) << 2))
#define MAP_HG(b) (((((b) >> 2) & 6) ^ (((b) & 32) ? 2 : 4)) | ((((b) >> 1) ^ ((b) >> 2) ^ ((b) >> 3) ^ ((b) >> 5) ^ 1) & 1))
#define SKEW 4
#define PACE 500
#define PACE_W0 (-600)
#define PACE_A 100
#define PACE_XA 25
#define T_SH 150
#define PACE_B 450
#define RG_T0 1700
#define RG_DT 200
#define GU_T0 3600
#define GU_DT 500
#define RS_T0 9200
#define RS_DT 200
#define HALO_D 250
#define PF_UP 7000
#define PF_DT 450
#define O_D 150
#define O_DT 300
#define C1_D 0
#define C2_D 0
#define C5_D 0
#define C6_D 100
#define C7_D 100
#define GH_DT 300
#define GX_D 400
#define Y_AT 1
#define CAND_T 8100
#define DN_D 0
#define GATE_T 9000
#define GH_T0 6800
#define NRS 2
#define DN0(q) ((q) * 3 - ((q) == 3))
#define WO_D ((uint64_t)(C1_D / 16) << 8 | (uint64_t)(C2_D / 16) * 0x10101 << 16 | (uint64_t)(C5_D / 16) << 40 | (uint64_t)(C6_D / 16) << 48 | (uint64_t)(C7_D / 16) << 56)

__device__ __forceinline__ unsigned block_id() { unsigned b; asm volatile("mov.u32 %0, %%ctaid.x;" : "=r"(b)); return b; }
__device__ __forceinline__ uint32_t keep(uint32_t v) { return __shfl_sync(0xffffffffu, v, threadIdx.x); }
__device__ __forceinline__ uint32_t ukeep(uint32_t v) { return __shfl_sync(0xffffffffu, v, 0); }
__device__ __forceinline__ void ldsm(uint32_t* d, uint32_t a) {
    asm volatile("ldmatrix.sync.aligned.m8n8.x4.shared.b16 {%0,%1,%2,%3}, [%4];"
                 : "=r"(d[0]), "=r"(d[1]), "=r"(d[2]), "=r"(d[3]) : "r"(a) : "memory");
}
__device__ __forceinline__ void stsm(uint32_t a, uint32_t x, uint32_t y, uint32_t z, uint32_t w) {
    asm volatile("stmatrix.sync.aligned.m8n8.x4.shared.b16 [%0], {%1,%2,%3,%4};" ::"r"(a), "r"(x), "r"(y), "r"(z), "r"(w) : "memory");
}
__device__ __forceinline__ void row_sums(float& sa, float& sb, float a0, float a1, float b0, float b1) {
    asm volatile("{\n.reg .f32 x, y;\nmma.sync.aligned.m16n8k8.row.col.f32.tf32.tf32.f32 {%0,x,%1,y}, {%2,%3,%4,%5}, {%6,%6}, {%7,%7,%7,%7};\n}"
                 : "=f"(sa), "=f"(sb) : "r"(f2u(a0)), "r"(f2u(b0)), "r"(f2u(a1)), "r"(f2u(b1)), "r"(0x3F800000), "f"(0.f));
}
template <bool SWP, int SEG, int E>
__device__ __forceinline__ void pack_blocks(uint32_t (&d)[10], const float (&am)[96], const float (&ar)[24]) {
#pragma unroll
    for (int t = 0; t < 10; t++) {
        const float* p = (SWP ? t < 2 : t >= 8) ? ar + (SEG * 2 + (t & 1)) * 4 + E : am + (SEG * 8 + t - (SWP ? 2 : 0)) * 4 + E;
        d[t] = pack2v(p[0], p[1]);
    }
}
#define HALF(hg) ((hg) >> 2)
#define CB(hg) ((hg) & 3)
constexpr int src_of(int i, int hg) {
    return i == 0 ? hg : (i - (i <= (hg | 4))) ^ (~hg & 4);
}

__device__ __forceinline__ uint32_t o_buf(int i) { return __byte_perm(0x5B000000u, 0x473D6F65u, i) << 10; }
__device__ constexpr uint32_t wo_buf(int i) { return SM_W + ((0x10546103u >> i * 4) & 7) * 30720; }

template <int N>
__device__ __forceinline__ void poll(uint4 (&a)[N], const uint4* p, int stride) {
    bool bad;
    do {
        bad = false;
#pragma unroll
        for (int s = 0; s < N; s++) a[s] = ld_relaxed16(p + s * stride);
#pragma unroll
        for (int s = 0; s < N; s++) bad |= a[s].w == SENT;
    } while (__any_sync(0xffffffffu, bad));
}
__device__ __forceinline__ void pace(unsigned t0, int t) {
    asm volatile("{\n.reg .pred p;\n.reg .s32 d;\nAGAIN:\nmov.u32 d, %%clock;\nsub.s32 d, d, %0;\nsetp.lt.s32 p, d, 0;\n"
                 "@p nanosleep.u32 20;\n@p bra AGAIN;\n}" ::"r"(t0 + t) : "memory");
}
__device__ __forceinline__ void l2_prefetch(const void* p) { asm volatile("prefetch.global.L2 [%0];" ::"l"(p) : "memory"); }

template <int ROW>
__device__ __forceinline__ void wgmma_vec(float (&d)[8], uint32_t a, uint32_t b, int scale_d) {
    asm volatile("{\n.reg .pred p;\n.reg .b64 da, db;\nsetp.ne.b32 p, %10, 0;\nmov.b64 da, {%8, 0x40000040};\nmov.b64 db, {%9, %11};\n"
                 "wgmma.mma_async.sync.aligned.m64n16k16.f32.bf16.bf16 {%0, %1, %2, %3, %4, %5, %6, %7}, da, db, p, 1, 1, 1, 0;\n}"
                 : "+f"(d[0]), "+f"(d[1]), "+f"(d[2]), "+f"(d[3]), "+f"(d[4]), "+f"(d[5]), "+f"(d[6]), "+f"(d[7])
                 : "r"(a), "r"(b), "r"(scale_d), "n"(ROW / 16));
}

__global__ void __launch_bounds__(512, 1) fused_kernel(const __grid_constant__ Params P) {
    extern __shared__ __align__(1024) uint8_t smem_raw[];
    const unsigned t_start = clock() - T_SH;
    const int tid = threadIdx.x, lane = tid & 31;
    const unsigned b0 = block_id();
    if (tid == 384) {
        const int tile = MAP_TILE(b0), hg = MAP_HG(b0), swp = (hg & 3) == 3;
        mbar_init(B_FULL, 1);
        asm volatile("fence.mbarrier_init.release.cluster;" ::: "memory");
        sts4(SM_PROF + 63 * 4, clock());
        tma_3d(SM_W, &P.w, B_FULL, hg * 80 + (swp ? 16 : 0), 0, 0);
        tma_3d(SM_X + 8192, &P.x, B_FULL, 0, tile & 1, (tile >> 1) * 128 + 64);
        tma_3d(SM_W + 12288, &P.wr, B_FULL, hg * 80 + (swp ? 0 : 64), 0, 0);
        mbar_init(B_XL0, 1);
        mbar_init(B_FULL + 8, 1);
        mbar_init(B_FULL + 16, 1);
        asm volatile("fence.mbarrier_init.release.cluster;" ::: "memory");
        tma_3d(SM_X, &P.x, B_XL0, 0, tile & 1, (tile >> 1) * 128);
        mbar_expect_tx(B_FULL, 15360 + 8192);
        mbar_expect_tx(B_XL0, 8192);
    }
    const int warp = __shfl_sync(0xffffffffu, tid >> 5, 0);
    if (warp < 8 && (warp & 3) && elect_one()) {
#pragma unroll
        for (int i = 0; i < 4; i++) mbar_init(SM_BAR + (warp - (warp >> 2)) * 32 + i * 8, warp < 4 ? 1 : warp < 7 ? 2 : 4);
        asm volatile("fence.mbarrier_init.release.cluster;" ::: "memory");
    }
    __syncthreads();
    const unsigned bx = block_id();
    const int tile = MAP_TILE(bx), hg = MAP_HG(bx);
    const int cid = tile * 8 + hg;
    const int par = tile & 1, p0 = (tile >> 1) * 128;
    uint4* const sc = g_sc + cid * SC_SIZE;
    const int fid = ((bx - 8) & 127) ^ (~bx >> 1 & 2);
    const bool swp = (hg & 3) == 3;
    const int wcm = hg * 80 + (swp ? 16 : 0), wcr = hg * 80 + (swp ? 0 : 64);
    if (warp == 12 && elect_one()) {
        mbar_expect_tx(B_FULL + 8, 15360);
        tma_3d(SM_W + 15360, &P.w, B_FULL + 8, wcm, 32, 0);
        tma_3d(SM_W + 15360 + 12288, &P.wr, B_FULL + 8, wcr, 32, 0);
        mbar_expect_tx(B_FULL + 16, 15360 + 16384);
        tma_3d(SM_W + 30720, &P.w, B_FULL + 16, wcm, 64, 0);
        tma_3d(SM_W + 30720 + 12288, &P.wr, B_FULL + 16, wcr, 64, 0);
    }

    if (warp >= 12) {
        asm volatile("setmaxnreg.dec.sync.aligned.u32 32;");
        if (warp == 12) {
            if (elect_one()) {
#pragma unroll 1
                for (int s = 3; s < 20; s++) {
                    const uint32_t fb = B_FULL + (s & 7) * 8, dst = SM_W + (s & 7) * 15360;
                    mbar_wait(fb + (B_EMPTY - B_FULL), ~(s >> 3) & 1);
                    pace(t_start, max(PACE_A + s * PACE_B, PACE_W0 + s * PACE));
                    mbar_expect_tx(fb, (s & 1) ? 15360 : 15360 + 16384);
                    tma_3d(dst, &P.w, fb, wcm, s * 32, 0);
                    tma_3d(dst + 12288, &P.wr, fb, wcr, s * 32, 0);
                    TS2(20 + s);
                }
                mbar_wait(B_RG2, 0);
                if (fid < NFFN) {
                    const int nd = 3 - (fid >> 1 & 1);
                    mbar_expect_tx(B_UP, 6144);
                    mbar_expect_tx(B_DN, nd * 8192);
                    mbar_wait(B_EMPTY + 4 * 8, 1);
                    TSQ(40);
                    tma_2d(SM_UP, &P.up2, B_UP, (fid >> 2) * 64, (fid & 3) * 160 + 112);
                    mbar_wait(B_EMPTY + 5 * 8, 1);
                    const unsigned t0 = clock();
#pragma unroll 1
                    for (int i = 0; i < nd; i++) {
                        pace(t0, i * DN_D);
                        tma_3d(SM_DN + i * 8192, &P.down, B_DN, 0, (fid >> 2) * 64, DN0(fid & 3) + i);
                    }
                    TSQ(41);
                }
                const int cb = CB(hg), ca = (cb * 5 + 1) >> 1, cr = cb * 160 + ((cb & 1) ? 0 : 128);
                unsigned t1 = 0;
#pragma unroll 1
                for (int j = 0; j < 8; j++) {
                    const int i = j ^ (j == 3 || j == 4 ? 7 : 0);
                    if (j != 3) mbar_wait(j < 3 ? B_EMPTY + ((2 * j + 7) & 7) * 8 : j == 5 ? B_HF : B_GUD + (j - 4) * 8, j == 0);
                    if (j != 3 && j != 4) t1 = clock();
                    pace(t1, (WO_D >> j * 8 & 255) * 16);
                    const uint32_t dst = wo_buf(i), gb = B_G2 + i * 8;
                    TSQ(20 + j);
                    mbar_expect_tx(gb, 25600);
                    tma_3d(dst, &P.woa, gb, 0, (P.src[hg] >> i * 4 & 7) * 80, ca);
                    tma_2d(dst + 20480, &P.wob, gb, cr, (P.src[hg] >> i * 4 & 7) * 80);
                }
            }
        } else if (warp == 14) {
            if (elect_one()) {
#pragma unroll 1
                for (int kb = 1; kb < 10; kb++) {
                    const uint32_t fb = B_FULL + (kb & 3) * 16, dst = SM_X + (kb & 3) * 16384;
                    mbar_wait(fb + (B_EMPTY - B_FULL + 8), ~(kb >> 2) & 1);
                    if (kb >= 4) mbar_wait(B_XE + (kb - 4 >> 1) * 8, 0);
                    pace(t_start, max(PACE_XA + 2 * kb * PACE_B, PACE_W0 - 50 + (2 * kb + 1) * PACE));
                    tma_3d(dst, &P.x2, fb, kb * 64, par, p0);
                }
            }
            __syncwarp();
            mbar_wait(B_ALL, 0);
            bar_sync(12, 64);
            pace(t_start, 0);
            pace(clock(), HALO_D);
            uint4 hv[5];
            poll<5>(hv, sc + (SC_HALO - (tile < 2 ? 0 : 16 * SC_SIZE) + lane), 32);
#pragma unroll
            for (int s = 0; s < 5; s++) sts16(SM_HALO + s * 512 + lane * 16, hv[s].x, hv[s].y, hv[s].z, hv[s].w);
            bar_arrive(8, 64);
            TSM(25);
        } else if (warp == 15) {
            int it = smem_u32(smem_raw) == SB ? 0 : 1 << 20;
            while (!mbar_try(B_XE + 16, 0))
                if (++it > (1 << 20)) fault();
            TSR(44);
            const uint32_t key = lds4(SM_KEY + (lane & 15) * 4), epoch = lds4(SM_KEY + 20 * 4);
            uint32_t k1 = __reduce_max_sync(0xffffffffu, key);
            uint32_t k2 = __reduce_max_sync(0xffffffffu, key == k1 ? 0u : key);
            if (elect_one()) {
                st_relaxed16(g_cand + cid, k1, k2, epoch, epoch);
                red_inc(g_cnt, epoch);
                TSR(45);
                if (fid < NFFN) {
                    mbar_expect_tx(B_GU, 10240);
                    pace(t_start, GH_T0);
                    tma_2d(SM_G, &P.up, B_GU, (fid >> 2) * 64, (fid & 3) * 160 + 32);
                    pace(clock(), GH_DT);
                    tma_2d(SM_G + 4096, &P.up2, B_GU, (fid >> 2) * 64, (fid & 3) * 160 + 64);
                }
            }
            __syncwarp();
            pace(t_start, CAND_T);
            TSR(46);
            uint4 cd[4];
            do {
                TSR(47);
#pragma unroll
                for (int j = 0; j < 4; j++) cd[j] = ld_relaxed16(g_cand + lane + 32 * j);
                if (++it > (1 << 20)) fault();
            } while (!__all_sync(0xffffffffu, cd[0].z == epoch && cd[1].z == epoch && cd[2].z == epoch && cd[3].z == epoch));
            TSR(48);
            uint32_t l1 = 0, l2 = 0;
#pragma unroll
            for (int j = 0; j < 4; j++) {
                l2 = max(max(l2, cd[j].y), min(l1, cd[j].x));
                l1 = max(l1, cd[j].x);
            }
            k1 = __reduce_max_sync(0xffffffffu, l1);
            k2 = __reduce_max_sync(0xffffffffu, l1 == k1 ? l2 : l1);
            if (elect_one()) {
                bulk_load(SM_XS, P.xp + (~k1 & 2047) * 640 + (fid & 3) * 160, 320, B_XS);
                bulk_load(SM_XS + 320, P.xp + (~k2 & 2047) * 640 + (fid & 3) * 160, 320, B_XS);
                sts16(SM_KEY + 16 * 4, k1, k2, 0, 0);
                mbar_expect_tx(B_XS, 640);
                mbar_arrive(B_ALL);
                TSR(49);
            }
            __syncwarp();
            while (!mbar_try(B_DONE, 0) || !mbar_try(B_MOD, 0))
                if (++it > (1 << 20)) fault();
        } else {
#pragma unroll 1
            for (int i = 0; i < 10; i++) sts16(SM_SENT + i * 512 + lane * 16, SENT, SENT, SENT, SENT);
            fence_async_smem();
            __syncwarp();
            if (elect_one()) {
                mbar_expect_tx(B_RG, 2560);
                asm volatile("mbarrier.expect_tx.relaxed.cta.shared::cta.b64 [%0], 10240;" ::"r"(B_RG2) : "memory");
                asm volatile("mbarrier.expect_tx.relaxed.cta.shared::cta.b64 [%0], 24576;" ::"r"(B_GU) : "memory");
                bulk_load(SM_RED, P.w_r, 1280, B_RG);
                bulk_load(SM_RED + 1280, P.gate_w, 1280, B_RG);
#pragma unroll
                for (int i = 0; i < 24; i++) mbar_init(B_GUD + i * 8, i == 23 ? 8 : i == 0 || i == 22 ? 4 : i < 15 + NRS ? 1 : 2);
#pragma unroll 1
                for (int i = 0; i < 5; i++) {
                    pace(t_start, RG_T0 + i * RG_DT);
                    tma_3d(SM_G + i * 2048, &P.xg, B_RG2, 320 + i * 64, par, p0 + hg * 16);
                }
                bulk_store(sc + SC_HALO, SM_SENT, 5120);
                asm volatile("cp.async.bulk.commit_group;\ncp.async.bulk.wait_group 0;" ::: "memory");
                mbar_arrive(B_RG2);
                TS(43);
#pragma unroll 1
                for (int i = 0; i < (fid < NFFN ? 6 : 0); i++) {
                    pace(t_start, GU_T0 + i * GU_DT);
                    tma_2d(SM_F + i * 4096, i < 5 ? &P.gate : &P.up, B_GU, (fid >> 2) * 64, (fid & 3) * 160 + (i < 5 ? i * 32 : 0));
                }
            }
            __syncwarp();
            if (fid < NFFN) {
                const __nv_bfloat16* up = P.upp + ((fid & 3) * 160 + 112 + lane) * 1728 + (fid >> 2) * 64;
                pace(t_start, PF_UP - PF_DT);
                l2_prefetch(up);
                l2_prefetch(up + 16 * 1728);
            }
            const unsigned goal = (ld_relaxed4(g_cnt + 32) | (NCTA - 1)) + 1;
            if (elect_one()) {
#pragma unroll 1
                for (int i = 0; i < 4; i++) {
                    pace(t_start, RS_T0 + i * RS_DT);
                    bulk_store(sc + i * 320, SM_SENT, 5120);
                }
                asm volatile("cp.async.bulk.commit_group;\ncp.async.bulk.wait_group 0;" ::: "memory");
                red_inc(g_cnt + 32, goal);
                mbar_arrive(B_RS);
            }
            __syncwarp();
            TSQ(30);
            while (ld_relaxed4(g_cnt + 32) - goal > 0x80000000u) {}
            if (lane == 0) mbar_arrive(B_INIT);
            TS(45);
        }
    } else if (warp >= 8) {
        asm volatile("setmaxnreg.dec.sync.aligned.u32 96;");
        const int t = tid - 256;
        const unsigned epoch = ld_relaxed4(g_cnt) / NCTA + 1;
        float gv = 0.f;
        int grow = hg * 16 + (t >> 3);
        {
            const uint32_t sw = (t >> 4) * 128 + (((t ^ (t >> 4)) & 7) << 4), hi = (t >> 3) & 1;
            const uint32_t xs = keep(sw + SM_X + hi * 16384 + hg * 2048), xg = keep(sw + SM_G + hi * 2048), ws = SM_RED + (t & 15) * 16;
            uint4 a[5], b[5], w[5];
            float r0 = 0.f, r1 = 0.f;
            auto load = [&](int p, uint32_t xa) { a[p] = lds16(xa); b[p] = lds16(xa + 1024); w[p] = lds16(ws + p * 256); };
            auto dot = [&](int p) {
                const uint32_t as[4] = {a[p].x, a[p].y, a[p].z, a[p].w}, bs[4] = {b[p].x, b[p].y, b[p].z, b[p].w};
                const uint32_t vs[4] = {w[p].x, w[p].y, w[p].z, w[p].w};
#pragma unroll
                for (int e = 0; e < 4; e++) {
                    r0 = fmaf(bf_lo(as[e]), bf_lo(vs[e]), r0);
                    r1 = fmaf(bf_lo(bs[e]), bf_lo(vs[e]), r1);
                    r0 = fmaf(bf_hi(as[e]), bf_hi(vs[e]), r0);
                    r1 = fmaf(bf_hi(bs[e]), bf_hi(vs[e]), r1);
                }
                asm volatile("" : "+f"(r0), "+f"(r1), "+r"(a[p].x), "+r"(a[p].y), "+r"(a[p].z), "+r"(a[p].w),
                                  "+r"(b[p].x), "+r"(b[p].y), "+r"(b[p].z), "+r"(b[p].w));
            };
            auto release = [&](int p) {
                if (__ballot_sync(0xffffffffu, lane == 0 || (a[p].w ^ w[p].w) == b[p].w) && lane == 0) mbar_arrive(B_XE + p * 8);
            };
            auto total = [&]() {
                float r = (hi ? r1 : r0) + __shfl_xor_sync(0xffffffffu, hi ? r0 : r1, 8);
                r += __shfl_xor_sync(0xffffffffu, r, 4);
                r += __shfl_xor_sync(0xffffffffu, r, 2);
                return bf_round(r + __shfl_xor_sync(0xffffffffu, r, 1));
            };
            mbar_wait(B_RG, 0);
            mbar_wait(B_XL0, 0);
            mbar_wait(B_FULL, 0);
            mbar_wait(B_FULL + 16, 0);
            TSR(32);
            load(0, xs);
            release(0);
            dot(0);
            TSR(33);
            mbar_wait(B_RG2, 0);
            TSR(34);
            load(3, xg + 2048);
            load(4, xg + 6144);
            mbar_wait(B_FULL + 32, 0);
            mbar_wait(B_FULL + 48, 0);
            TSR(35);
            load(1, xs + 32768);
            dot(3);
            release(1);
            dot(4);
            TSR(36);
            mbar_wait(B_FULL, 1);
            TSR(37);
            load(2, hi ? xg - 2048 : xs);
            dot(1);
            dot(2);
            TSR(42);
            grow = hg * 16 + (t >> 4) + hi * 8;
            const uint32_t u = f2u(total());
            sts4(SM_KEY + (t >> 3) * 4, (((int)u < 0 ? ~u : u | 0x80000000u) & 0xFFFF0000u) | (2047 - (p0 + grow) * 2 - par));
            sts4(SM_KEY + 20 * 4, epoch);
            __syncwarp();
            if (lane == 0) mbar_arrive(B_XE + 16);
            TSR(43);
            r0 = r1 = 0.f;
#pragma unroll
            for (int p = 0; p < 5; p++) w[p] = lds16(ws + 1280 + p * 256);
#pragma unroll
            for (int p = 0; p < 5; p++) dot(p);
            gv = total();
        }
        if ((lane & 7) == 4) st_relaxed4(g_gate + tile * 128 + grow, f2u(bf_round(sigmoidf(gv))) | (epoch & 0xFFFFu));
        TSR(38);
        if (warp == 9) {
            pace(t_start, GATE_T);
            uint4 v;
            do {
                asm volatile("ld.relaxed.gpu.global.v4.u32 {%0, %1, %2, %3}, [%4];"
                             : "=r"(v.x), "=r"(v.y), "=r"(v.z), "=r"(v.w) : "l"(g_gate + tile * 128 + lane * 4) : "memory");
            } while (__any_sync(0xffffffffu, ((v.x ^ epoch) | (v.y ^ epoch) | (v.z ^ epoch) | (v.w ^ epoch)) & 0xFFFFu));
            sts16(SM_GATE + lane * 16, v.x & 0xFFFF0000u, v.y & 0xFFFF0000u, v.z & 0xFFFF0000u, v.w & 0xFFFF0000u);
            __syncwarp();
            if (lane == 0) mbar_arrive(B_GT);
        }
        mbar_wait(B_XS, 0);
        TS(warp == 8 ? 50 : 63);
        TSR(50);
        const int cq = lane & 3, q = fid & 3;
        if (fid < NFFN) {
            uint4* const sc = g_sc + fid * SC_SIZE;
            float ga[8], ua[8];
            mbar_wait(B_GU, 0);
            TS(warp == 8 ? 61 : 63);
            mbar_wait(B_UP, 0);
            TSR(52);
            bar_sync(13, 256);
            TSM(warp == 8 ? 53 : 63);
            wg_fence();
#pragma unroll
            for (int i = 0; i < 10; i++) {
                wgmma_vec<320>(ga, desc_lo(SM_F, 16) + i * 128, desc_lo(SM_XS, 16) + i * 2, i);
                wgmma_vec<320>(ua, desc_lo(i < 7 ? SM_F + 20480 : SM_UP - 14336, 16) + i * 128, desc_lo(SM_XS, 16) + i * 2, i);
            }
            wg_commit();
            wg_wait<0>();
            TSM(warp == 8 ? 54 : 63);
            if (cq == 0) {
                st_relaxed16(sc + SC_GU + (t >> 2), f2u(ga[0]), f2u(ga[2]), f2u(ga[4]), f2u(ga[6]));
                st_relaxed16(sc + SC_GU + 32 + (t >> 2), f2u(ua[0]), f2u(ua[2]), f2u(ua[4]), f2u(ua[6]));
            }
            if (lane == 0) mbar_arrive(B_GUD);
            uint4 pq[2];
            pace(clock(), GX_D);
            poll<2>(pq, sc + (cq - q) * SC_SIZE + SC_GU + (t >> 2), 32);
            TSR(55);
            const bool tk = cq & 2, c8 = cq & 1;
            float v[4];
#pragma unroll
            for (int m = 0; m < 2; m++) {
                v[2 * m] = u2f(tk ? pq[m].z : pq[m].x) + __shfl_xor_sync(0xffffffffu, u2f(tk ? pq[m].x : pq[m].z), 2);
                v[2 * m + 1] = u2f(tk ? pq[m].w : pq[m].y) + __shfl_xor_sync(0xffffffffu, u2f(tk ? pq[m].y : pq[m].w), 2);
                v[m] = bf_round((c8 ? v[2 * m + 1] : v[2 * m]) + __shfl_xor_sync(0xffffffffu, c8 ? v[2 * m] : v[2 * m + 1], 1));
            }
            const uint32_t h = pack2(bf_round(v[0] * sigmoidf(v[0])) * v[1], 0.f);
            asm volatile("st.shared.u16 [%0], %1;" ::"r"(SM_XS + (cq >> 1) * 128 + ((t >> 5) * 16 + (cq & 1) * 8 + (lane >> 2)) * 2),
                         "h"((uint16_t)h) : "memory");
            fence_async_smem();
            bar_sync(4, 128);
            TS(warp == 8 ? 57 : 63);
            mbar_wait(B_DN, 0);
            bar_sync(14, 384);
            TSR(56);
            float y[3][8];
#pragma unroll 1
            for (int i = 0; i < 4; i++) {
                wg_fence();
#pragma unroll
                for (int m = 0; m < 3; m++)
                    wgmma_vec<128>(y[m], desc_lo(SM_DN + m * 8192, 16) + i * 128, desc_lo(SM_XS, 16) + i * 2, i);
                wg_commit();
            }
            wg_wait<0>();
            if (cq == 0) {
#pragma unroll
                for (int m = 0; m < 6; m++)
                    asm volatile("st.relaxed.gpu.global.v2.f32 [%0], {%1, %2};"
                                 ::"l"(reinterpret_cast<float2*>(sc + SC_Y) + (m & 1) * 96 + (m >> 1) * 32 + (t >> 2)),
                                   "f"(y[m >> 1][(m & 1) * 4]), "f"(y[m >> 1][(m & 1) * 4 + 2]) : "memory");
            }
        } else if (lane == 0) {
            mbar_arrive(B_GUD);
        }
        if (lane == 0) mbar_arrive(B_DD);
        TSM(warp == 8 ? 51 : 63);
        const uint32_t k1 = lds4(SM_KEY + 16 * 4), k2 = lds4(SM_KEY + 17 * 4);
        const uint32_t mine = (tile >> 1) * 256 + HALF(hg) * 128 + par;
        const bool own1 = (~k1 & 0x781) == mine, own2 = (~k2 & 0x781) == mine;
        if ((own1 || own2) && NFFN) {
            const int rg = min(t / 40, 2), c40 = t % 40, un = CB(hg) * 40 + c40, src = un < 48 ? 0 : un < 96 ? 1 : un < 128 ? 2 : 3;
            const int col = min(t >> 3, 9) * 16 + (t & 1) * 8 + (t & 6);
            mbar_wait(B_OE + Y_AT * 8, 0);
            TS(warp == 8 ? 60 : 63);
#pragma unroll 1
            for (int j = !own1; j <= own2; j++) {
                const uint4* p = g_sc + (rg * 4 + src) * SC_SIZE + SC_Y + j * 48 + un - DN0(src) * 16;
                const uint32_t key = j ? k2 : k1;
                const uint32_t xv = *reinterpret_cast<const uint32_t*>(P.xp + (~key & 2047) * 640 + CB(hg) * 160 + col);
                float y[4];
                bool bad;
                do {
                    uint4 yp[9];
#pragma unroll
                    for (int i = 0; i < 9; i++) yp[i] = ld_relaxed16(p + i * 12 * SC_SIZE);
                    y[0] = y[1] = y[2] = y[3] = 0.f;
                    bad = false;
#pragma unroll
                    for (int i = 0; i < 9; i++) {
                        y[0] += u2f(yp[i].x); y[1] += u2f(yp[i].y); y[2] += u2f(yp[i].z); y[3] += u2f(yp[i].w);
                        bad |= max(max(yp[i].x, yp[i].y), max(yp[i].z, yp[i].w)) == SENT;
                    }
                } while (__any_sync(0xffffffffu, bad));
                TS(warp == 8 ? 62 : 63);
                sts16(SM_Y + j * 2048 + t * 16, f2u(y[0]), f2u(y[1]), f2u(y[2]), f2u(y[3]));
                bar_sync(4, 128);
                if (t < 80) {
                    const uint32_t ya = SM_Y + j * 2048 + (t >> 1) * 16 + (t & 1) * 4;
                    const float rs = bf_round(sigmoidf(u2f(((int)key < 0 ? key & 0x7FFFFFFFu : ~key) & 0xFFFF0000u)));
                    const float y0 = u2f(lds4(ya)) + u2f(lds4(ya + 640)) + u2f(lds4(ya + 1280));
                    const float y1 = u2f(lds4(ya + 8)) + u2f(lds4(ya + 648)) + u2f(lds4(ya + 1288));
                    sts4(SM_U + j * 320 + t * 4, hadd2(xv, pack2(bf_round(y0) * rs, bf_round(y1) * rs)));
                }
            }
            const int cc = col + (CB(hg) & 1 ? (col < 32 ? 128 : -32) : 0);
            mbar_wait(B_GT, 0);
#pragma unroll 1
            for (int j = !own1; j <= own2; j++) {
                const uint32_t tk = ~(j ? k2 : k1) & 2047, rr = tk >> 1 & 15, stg = SM_OUT + (tk >> 5 & 3) * 5120;
                const float n = 1.f - u2f(lds4(SM_GATE + (tk & 254) * 2));
                uint32_t u = lds4(SM_U + j * 320 + t * 4), nn = pack2(n, n), ca = stg + rr * 128 + (rr & 7) * 16;
                uint32_t aa = stg + (cc & 6) * 2 + (cc < 128 ? (cc >> 6) * 2048 + rr * 128 + (((cc >> 3 ^ rr) & 7) << 4)
                                                             : 4096 + rr * 64 + (((cc >> 3 ^ rr >> 1) & 3) << 4));
                __nv_bfloat16* dst = P.op + tk * 640 + CB(hg) * 160 + col;
                asm volatile("" : "+r"(u), "+r"(nn), "+r"(ca), "+r"(aa), "+l"(dst));
                mbar_wait(B_DONE, 0);
                const float chk = u2f(lds4(ca));
                uint32_t a = lds4(aa);
                if (chk != chk) {
                    mbar_wait(B_OE + 24, 0);
                    a = lds4(aa);
                }
                if (t < 80) *reinterpret_cast<uint32_t*>(dst) = hfma2(nn, u, a);
            }
        }
        if (t == 0) mbar_arrive(B_MOD);
        TS(warp == 8 ? 52 : 63);
    } else {
        asm volatile("setmaxnreg.inc.sync.aligned.u32 192;");
        const int wg = warp >> 2;
        const bool leader = (tid & 127) == 0;
        bool rel = false;
        uint32_t nb[40];
        const int odd = CB(hg) & 1, kba = ukeep(wg == HALF(hg) ? (CB(hg) * 5 + 1) >> 1 : 16), kbr = ukeep(kba + 2 - odd * 3);
        const int kbs = wg ? -1 : (20 - SKEW) / 2;
        const uint32_t xrow = keep(SM_X + (warp * 16 + (lane & 15)) * 128 + (((lane >> 4) ^ (lane & 7)) << 4));
        const uint32_t xr4 = keep((xrow ^ odd * 64) + (kbr & 3) * 16384), xr5 = keep(xr4 ^ 32);
        uint32_t xq[8];
        const int klo = ukeep(kba - odd);
#pragma unroll
        for (int i = 0; i < 8; i++) xq[i] = keep((xrow ^ (i & 3) * 32) + ((kba + (i >> 2)) & 3) * 16384);
        const int w4 = warp & 3, r = lane >> 2, cq = lane & 3;
        float am[96], ar[24];
        TSM(warp == 0 ? 3 : 63);
        if (wg == 0) mbar_wait(B_XL0, 0);
#pragma unroll 1
        for (int kb = 0; kb < 10; kb++) {
            const uint32_t fb = B_FULL + (kb & 3) * 16, wo = (kb & 3) * 1920, ph = (kb >> 2) & 1;
            const uint32_t xo = desc_lo(SM_X, 16) + wg * 512 + (kb & 3) * 1024;
#pragma unroll
            for (int h = 0; h < 2; h++) {
                mbar_wait(fb + h * 8, ph);
                if (kb == 0 && h == 0) TS(warp == 0 ? 0 : warp == 4 ? 16 : 63);
                TS2(warp == 4 ? kb * 2 + h : 63);
                if (h == 1 && (unsigned)(kb - klo) < 3) {
                    if (kb == kba) { ldsm(nb, xq[0]); ldsm(nb + 4, xq[1]); ldsm(nb + 8, xq[2]); ldsm(nb + 12, xq[3]); }
                    else if (kb == kbr) { ldsm(nb + 32, xr4); ldsm(nb + 36, xr5); }
                    else { ldsm(nb + 16, xq[4]); ldsm(nb + 20, xq[5]); ldsm(nb + 24, xq[6]); ldsm(nb + 28, xq[7]); }
                }
                wg_wait<1>();
                if (rel) mbar_arrive(B_EMPTY + ((kb * 16 - 16) & 48) + h * 8);
                if (h == (SKEW & 1) && kb == kbs) bar_sync(5, 256);
                wg_fence();
                wgmma_main(am, xo + h * 4, desc_lo(SM_W + h * 15360, 4096) + wo, h || kb);
                wgmma_rem(ar, xo + h * 4, desc_lo(SM_W + h * 15360 + 12288, 1024) + wo, h || kb);
                wgmma_main(am, xo + h * 4 + 2, desc_lo(SM_W + h * 15360 + 2048, 4096) + wo, 1);
                wgmma_rem(ar, xo + h * 4 + 2, desc_lo(SM_W + h * 15360 + 12288 + 512, 1024) + wo, 1);
                wg_commit();
            }
            rel = leader;
        }
        if (wg == 1) bar_arrive(5, 256);
        if (wg == 0) bar_arrive(13, 256);
        mbar_wait(B_EMPTY + 7 * 8 - wg * 16, 1);
        wg_wait<0>();
        if (rel) mbar_arrive(B_EMPTY + 3 * 8);
        TSM(warp == 0 ? 2 : warp == 4 ? 18 : 63);

        uint32_t kl[10], kh[10], vl[10], vh[10], ql[10], qh[10], kp[10], vp[10];
        if (swp) {
            pack_blocks<true, 1, 2>(kh, am, ar);
            pack_blocks<true, 2, 2>(vh, am, ar);
        } else {
            pack_blocks<false, 1, 2>(kh, am, ar);
            pack_blocks<false, 2, 2>(vh, am, ar);
        }
        const uint32_t pbuf = (wg ? SM_HALO1 : SM_HALO) + w4 * 2560 + lane * 16;
        const uint32_t hbuf = warp == 3 ? SM_HALO1 + lane * 16 : pbuf + 2560;
        {
            const uint32_t ex[20] = {kh[0], kh[1], kh[3], kh[4], kh[5], kh[6], kh[8], kh[9], kh[2], kh[7],
                                     vh[0], vh[1], vh[2], vh[3], vh[4], vh[5], vh[6], vh[7], vh[8], vh[9]};
            if (warp == 7) {
                uint4* const hp = sc + SC_HALO + lane;
#pragma unroll
                for (int s = 0; s < 5; s++) st_relaxed16(hp + s * 32, ex[4 * s], ex[4 * s + 1], ex[4 * s + 2], ex[4 * s + 3]);
                bar_arrive(12, 64);
            } else {
#pragma unroll
                for (int s = 0; s < 5; s++) sts16(hbuf + s * 512, ex[4 * s], ex[4 * s + 1], ex[4 * s + 2], ex[4 * s + 3]);
            }
        }
        if (warp == 3) bar_arrive(11, 64);
        if (swp) {
            pack_blocks<true, 2, 0>(vl, am, ar);
            pack_blocks<true, 0, 0>(ql, am, ar);
            pack_blocks<true, 0, 2>(qh, am, ar);
            pack_blocks<true, 1, 0>(kl, am, ar);
        } else {
            pack_blocks<false, 2, 0>(vl, am, ar);
            pack_blocks<false, 0, 0>(ql, am, ar);
            pack_blocks<false, 0, 2>(qh, am, ar);
            pack_blocks<false, 1, 0>(kl, am, ar);
        }
#pragma unroll
        for (int t = 0; t < 10; t++) { vl[t] = movm(vl[t]); vh[t] = movm(vh[t]); }
        mbar_wait(B_RS, 0);
        mbar_wait(B_GT, 0);
        const float g0 = u2f(lds4(SM_GATE + warp * 64 + (lane & 28))), g1 = u2f(lds4(SM_GATE + 32 + warp * 64 + (lane & 28)));

        const bool no_prev = warp == 0 && tile < 2, low = cq < 2;
        const bool le0 = 2 * cq <= r, le1 = 2 * cq + 1 <= r;
        const uint32_t mle = (le0 ? 0xFFFFu : 0u) | (le1 ? 0xFFFF0000u : 0u);
        const float scl = 0.22360679774997896f * 1.4426950408889634f;
        uint32_t pl[4], ph[4], ol[10], oh[10], cl = 0;
        {
            float sl[4][4], sh[4][4], sp[4][4];
            bar_sync(6 + wg, 128);
            if (w4 == 0) bar_sync(8 + wg * 3, 64);
            {
                const uint4 a = lds16(pbuf), b = lds16(pbuf + 512), c = lds16(pbuf + 1024), d = lds16(pbuf + 1536), e = lds16(pbuf + 2048);
                kp[0] = a.x; kp[1] = a.y; kp[3] = a.z; kp[4] = a.w; kp[5] = b.x; kp[6] = b.y; kp[8] = b.z; kp[9] = b.w;
                kp[2] = c.x; kp[7] = c.y; vp[0] = c.z; vp[1] = c.w; vp[2] = d.x; vp[3] = d.y; vp[4] = d.z; vp[5] = d.w;
                vp[6] = e.x; vp[7] = e.y; vp[8] = e.z; vp[9] = e.w;
            }
#pragma unroll
            for (int h = 0; h < 4; h++) {
                const int ta = (h >> 1) * 5 + (h & 1) * 3, tc = (h >> 1) * 5 + 2;
                const uint32_t ml = low != (h & 1) ? ql[tc] : 0u, mh = low != (h & 1) ? qh[tc] : 0u;
#pragma unroll
                for (int e = 0; e < 4; e++) sl[h][e] = sh[h][e] = sp[h][e] = 0.f;
                mma16(sl[h], ql[ta], qh[ta], ql[ta + 1], qh[ta + 1], kl[ta], kl[ta + 1]);
                mma16(sh[h], ql[ta], qh[ta], ql[ta + 1], qh[ta + 1], kh[ta], kh[ta + 1]);
                mma8(sl[h], ml, mh, kl[tc]);
                mma8(sh[h], ml, mh, kh[tc]);
            }
#pragma unroll
            for (int h = 0; h < 4; h++) {
                const int ta = (h >> 1) * 5 + (h & 1) * 3, tc = (h >> 1) * 5 + 2;
                mma16(sp[h], ql[ta], qh[ta], ql[ta + 1], qh[ta + 1], kp[ta], kp[ta + 1]);
                mma8(sp[h], low != (h & 1) ? ql[tc] : 0u, low != (h & 1) ? qh[tc] : 0u, kp[tc]);
            }
#pragma unroll
            for (int t = 0; t < 10; t++) vp[t] = movm(vp[t]);
#pragma unroll
            for (int h = 0; h < 4; h++) {
                if (no_prev) sp[h][0] = sp[h][1] = -1e9f / 0.22360679774997896f;
                float a0 = le0 ? sl[h][0] : sp[h][0], a1 = le1 ? sl[h][1] : sp[h][1];
                float b0 = le0 ? sh[h][2] : sl[h][2], b1 = le1 ? sh[h][3] : sl[h][3];
                float ma = fmaxf(a0, a1), mb = fmaxf(b0, b1);
                ma = fmaxf(ma, __shfl_xor_sync(0xffffffffu, ma, 1));
                mb = fmaxf(mb, __shfl_xor_sync(0xffffffffu, mb, 1));
                ma = fmaxf(ma, __shfl_xor_sync(0xffffffffu, ma, 2));
                mb = fmaxf(mb, __shfl_xor_sync(0xffffffffu, mb, 2));
                ma *= -scl;
                mb *= -scl;
                a0 = ex2(fmaf(a0, scl, ma)), a1 = ex2(fmaf(a1, scl, ma));
                b0 = ex2(fmaf(b0, scl, mb)), b1 = ex2(fmaf(b1, scl, mb));
                row_sums(ma, mb, a0, a1, b0, b1);
                ma = rcp(ma) * g0;
                mb = rcp(mb) * g1;
                pl[h] = pack2(a0 * ma, a1 * ma);
                ph[h] = pack2(b0 * mb, b1 * mb);
            }
            uint32_t* const po = reinterpret_cast<uint32_t*>(sc + SC_O + warp * 160) + lane;
#pragma unroll
            for (int hp = 0; hp < 2; hp++) {
                float o[6][4];
#pragma unroll
                for (int h = 0; h < 2; h++) {
                    const int ta = hp * 5 + h * 3, tc = hp * 5 + 2;
                    const uint32_t a0 = pl[hp * 2 + h] & mle, a1 = ph[hp * 2 + h] & ~mle, a3 = ph[hp * 2 + h] & mle, ap = pl[hp * 2 + h] & ~mle;
#pragma unroll
                    for (int i = 0; i < 3; i++) o[h * 3 + i][0] = o[h * 3 + i][1] = o[h * 3 + i][2] = o[h * 3 + i][3] = 0.f;
#pragma unroll
                    for (int i = 0; i < 3; i++) mma8(o[h * 3 + i], a0, a1, vl[i < 2 ? ta + i : tc]);
#pragma unroll
                    for (int i = 0; i < 3; i++) mma16(o[h * 3 + i], ap, 0u, 0u, a3, vp[i < 2 ? ta + i : tc], vh[i < 2 ? ta + i : tc]);
                }
#pragma unroll
                for (int i = 0; i < 2; i++) {
                    ol[hp * 5 + i] = pack2(o[i][0], o[i][1]);
                    oh[hp * 5 + i] = pack2(o[i][2], o[i][3]);
                    ol[hp * 5 + 3 + i] = pack2(o[3 + i][0], o[3 + i][1]);
                    oh[hp * 5 + 3 + i] = pack2(o[3 + i][2], o[3 + i][3]);
                }
                ol[hp * 5 + 2] = pack2(low ? o[2][0] : o[5][0], low ? o[2][1] : o[5][1]);
                oh[hp * 5 + 2] = pack2(low ? o[2][2] : o[5][2], low ? o[2][3] : o[5][3]);
#pragma unroll
                for (int t = hp * 5; t < hp * 5 + 5; t++) {
                    st_relaxed4(po + t * 32, ol[t]);
                    st_relaxed4(po + t * 32 + 320, oh[t]);
                    if (t == 5) {
                        if (wg != HALF(hg)) bar_arrive(2, 256);
                        bar_arrive(14, 384);
                        if (lane == 0) mbar_arrive(B_HF);
                    }
                }
                if (!hp) cl = clock();
            }
        }
        TSM(warp == 0 ? 5 : warp == 4 ? 21 : warp == 5 ? 30 : warp == 1 ? 31 : warp == 2 ? 32 : warp == 3 ? 33 : warp == 6 ? 34 : 24);
        const uint4* ow = sc + (SC_O + HALF(hg) * 640 - hg * SC_SIZE);
        auto stage = [&]() {
            mbar_wait(B_INIT, 0);
            mbar_wait(B_OE, 0);
            const unsigned t0 = clock();
            uint32_t ph = 0;
#pragma unroll 1
            for (int i = w4 + 1 + NRS; i < 8; i += 4) {
                const uint4* src = ow + (P.src[hg] >> i * 4 & 7) * SC_SIZE;
                const uint32_t buf = o_buf(i), chk = buf + lane * 132;
                if (i >= 6) mbar_wait(B_DD, 0);
                pace(t0, (i - 3) * O_DT + O_D);
                uint32_t c;
                do {
                    if (elect_one()) {
                        mbar_expect_tx(B_OT + w4 * 8, 10240);
                        bulk_load(buf, src, 10240, B_OT + w4 * 8);
                    }
                    mbar_wait(B_OT + w4 * 8, ph);
                    if (i == 1 + NRS && !ph) TS(wg ? 19 : 20);
                    ph ^= 1;
                    c = max(max(lds4(chk), lds4(chk + 4096)), lds4(chk + 6144));
                } while (__any_sync(0xffffffffu, c == SENT));
                if (lane == 0) mbar_arrive(B_G2 + i * 8);
                TSM(32 + i);
            }
        };
        const bool idle = wg != HALF(hg);

        float oc[80];
        uint32_t routed = ~0u, n0, n1, stg, m128 = SM_SENT + lane * 16, m64 = m128, l128 = m128, l64 = m128, oa128, oa64;
        int orow;
        char *o128, *o64;
        bool nan;
        uint32_t c3 = 0;
        if (!idle || w4 == 3) {
        if (!idle) {
        uint32_t af[2][20];
        const uint32_t* const ap = reinterpret_cast<const uint32_t*>(ow + (~hg & 4) * SC_SIZE + w4 * 160) + lane;
        auto fetch = [&](int i) {
#pragma unroll
            for (int t = 0; t < 20; t++) af[i & 1][(t >> 1) + (t & 1) * 10] = ld_relaxed4(ap + i * SC_SIZE * 4 + ((t >> 1) + (t & 1) * 10) * 32);
        };
        auto missing = [&](int i, uint32_t c) {
            uint32_t m[3] = {af[i][0], af[i][1], ((uint32_t)clock() | c) >> 1};
#pragma unroll
            for (int t = 2; t < 20; t++) m[t / 2 % 3] = max(m[t / 2 % 3], af[i][t]);
            return __any_sync(0xffffffffu, max(max(m[0], m[1]), m[2]) == SENT);
        };
        auto addresses = [&](uint4 kv, uint32_t c2) {
            const uint32_t ln = lane + kv.z;
            orow = p0 + wg * 64 + w4 * 16;
            const uint32_t otok = orow * 2 + par, d1 = (~kv.x & 2047) - otok, d2 = (~kv.y & 2047) - otok;
            routed = (shl(~d1 & 1, d1 >> 1) | shl(~d2 & 1, d2 >> 1) | c2 << 16) & 0x7FFFFFFFu;
            n0 = routed >> r & 1 ? 0 : pack2(1.f - g0, 1.f - g0), n1 = routed >> r & 256 ? 0 : pack2(1.f - g1, 1.f - g1);
            stg = SM_OUT + w4 * 5120;
            m128 = stg + (ln & 15) * 128 + (((ln >> 4) ^ (ln & 7)) << 4);
            m64 = stg + 4096 + (ln & 15) * 64 + (((ln >> 4) ^ ((ln >> 1) & 3)) << 4);
            l128 = stg + (ln ^ (ln >> 3)) * 16;
            l64 = l128 + 4096;
            oa128 = otok * 1280 + kba * 128 + (ln >> 3) * (2560 - 128) + ln * 16;
            oa64 = otok * 1280 + kbr * 128 + odd * 64 + (ln >> 2) * (2560 - 64) + ln * 16;
            asm volatile("" : "+r"(n0), "+r"(n1), "+r"(routed), "+r"(m128), "+r"(m64), "+r"(l128), "+r"(oa128), "+r"(oa64));
            l64 = l128 + 4096;
        };
        auto step = [&](int i, int s) {
            wgmma_reg(oc, af[i][2 * s], af[i][10 + 2 * s], af[i][2 * s + 1], af[i][11 + 2 * s], desc_lo(wo_buf(i + 1), 10240) + s * 128, 1);
        };
        bar_sync(2, 256);
        mbar_wait(B_G2, 0);
        TSM(w4 == 0 ? 6 : 63);
        wg_fence();
#pragma unroll
        for (int s = 0; s < 5; s++)
            wgmma_reg(oc, ol[2 * s], oh[2 * s], ol[2 * s + 1], oh[2 * s + 1], desc_lo(wo_buf(0), 10240) + s * 128, s);
        wg_commit();
        mbar_wait(B_XS, 0);
        mbar_wait(B_INIT, 0);
        TSM(40 + w4);
        int nit = 0;
        const uint4 kv = lds16(SM_KEY + 64);
        fetch(0);
        uint32_t c1 = clock() | cl;
        wg_wait<0>();
        if (leader) mbar_arrive(B_OE);
        fetch(1);
        addresses(kv, clock());
        nit++;
        if (__builtin_expect(missing(0, c1), 0)) do {
            fetch(0);
            c1 = clock();
            fetch(1);
            nit++;
        } while (missing(0, c1));
        TSM(44 + w4);
        mbar_wait(B_G2 + 8, 0);
        TSM(w4 == 0 ? 7 : 63);
        wg_fence();
#pragma unroll
        for (int s = 0; s < 4; s++) step(0, s);
        const bool again = missing(1, 0);
        c1 = clock();
        step(0, 4);
        wg_commit();
        if (__builtin_expect(again, 0)) do fetch(1); while (missing(1, 0));
        TSM(56 + w4);
        mbar_wait(B_G2 + 16, 0);
        TSM(w4 == 0 ? 11 : 63);
        wg_fence();
#pragma unroll
        for (int s = 0; s < 5; s++) step(1, s);
        wg_commit();
        c3 = c1;
        wg_wait<1>();
        if (leader) mbar_arrive(B_OE + 8);
#pragma unroll 1
        for (int i = 3; i < 8; i++) {
            const uint32_t ao = desc_lo(0, 128) + (o_buf(i) >> 4), wo = desc_lo(0, 10240) + (wo_buf(i) >> 4);
            mbar_wait(B_G2 + i * 8, 0);
            TSM(w4 == 0 ? (i < 7 ? 9 + i : 17) : 63);
            wg_fence();
#pragma unroll
            for (int s = 0; s < 5; s++) wgmma_out64(oc, ao + s * 16, wo + s * 128, 1);
            wg_commit();
#pragma unroll
            for (int s = 0; s < 5; s++) wgmma_out96(oc, ao + s * 16, wo + 640 + s * 128, 1);
            wg_commit();
            if (i == 3) {
                wg_wait<2>();
                if (leader) mbar_arrive(B_OE + 16);
            }
        }
        o128 = reinterpret_cast<char*>(P.op) + oa128;
        o64 = reinterpret_cast<char*>(P.op) + oa64;
        TS(w4 == 0 ? 8 : 63);

        wg_wait<1>();
        TSM(w4 == 0 ? 9 : 63);
        }
        const bool rt0 = routed >> r & 1, rt1 = routed >> r & 256;
#pragma unroll
        for (int pi = 0; pi < 3; pi++) {
            const int part = pi < 2 ? 1 - pi : pi;
            if (pi == 1) {
                c3 |= clock();
                wg_wait<0>();
            }
            const int s0 = part ? part * 4 - 4 : 8, ns = part ? 4 : 2;
#pragma unroll
            for (int i = 0; i < 4; i++) {
                if (i >= ns) break;
                const int s = s0 + i;
                const uint32_t y0 = hfma2(n0, nb[s * 4], pack2(oc[s * 8 + 0], oc[s * 8 + 1]));
                const uint32_t y1 = hfma2(n1, nb[s * 4 + 1], pack2(oc[s * 8 + 2], oc[s * 8 + 3]));
                const uint32_t y2 = hfma2(n0, nb[s * 4 + 2], pack2(oc[s * 8 + 4], oc[s * 8 + 5]));
                const uint32_t y3 = hfma2(n1, nb[s * 4 + 3], pack2(oc[s * 8 + 6], oc[s * 8 + 7]));
                if (s == 0) nan = u2f(y0) != u2f(y0) || u2f(y1) != u2f(y1);
                stsm(((s < 8 ? m128 : m64) ^ ((s & 3) * 32)) + (s & 4) * 512, y0, y1, y2, y3);
            }
            __syncwarp();
            if (pi == 2 && lane == 0 && (int)routed >= 0) mbar_arrive(B_DONE);
            uint4 v[4];
#pragma unroll
            for (int i = 0; i < 4; i++)
                if (i < ns) v[i] = lds16(!part ? l64 + i * 512 : (l128 ^ ((i & 1) * 64)) + i * 512 + s0 * 512);
#pragma unroll
            for (int i = 0; i < 4; i++)
                if (i < ns && !(part ? routed >> (lane >> 3) & 1 << 4 * i : i ? rt1 : rt0))
                    *reinterpret_cast<uint4*>(!part ? o64 + i * 8 * 2560 : o128 + i * 4 * 2560 + s0 * 32) = v[i];
            if (pi == 0) TS(w4 == 0 ? 1 : 63);
        }
        TSM(w4 == 0 ? 10 : idle ? 62 : 63);
        }
        if (idle) {
            stage();
            return;
        }
        const bool rt0 = routed >> r & 1, rt1 = routed >> r & 256;
        uint32_t redo;
        asm volatile("{\n.reg .pred p, q;\nsetp.eq.u32 p, %1, 0xFFFFFFFF;\nbar.cta.red.or.pred q, 10, 128, p;\nselp.u32 %0, 1, 0, q;\n}"
                     : "=r"(redo) : "r"(nan ? SENT : c3 >> 1) : "memory");
        if (redo) {
            const int cb = CB(hg);
#pragma unroll 1
            for (int i = 0; i < 8; i++) {
                if (leader) {
                    mbar_expect_tx(B_RE, 25600);
                    tma_3d(SM_W, &P.woa, B_RE, 0, i * 80, (cb * 5 + 1) >> 1);
                    tma_2d(SM_W + 20480, &P.wob, B_RE, cb * 160 + ((cb & 1) ? 0 : 128), i * 80);
                }
#pragma unroll 1
                for (int s = 0; s < 20; s++) {
                    const int w = w4 * 640 + s * 32 + lane;
                    uint32_t v, it = 0;
                    do {
                        v = ld_relaxed4(reinterpret_cast<const uint32_t*>(ow + i * SC_SIZE) + w);
                        if (++it > (1u << 22)) fault();
                    } while ((v >> 16) == 0xFFFFu || (v & 0xFFFFu) == 0xFFFFu);
                    sts4(SM_X + w * 4, v);
                }
                fence_async_smem();
                __syncwarp();
                bar_sync(10, 128);
                mbar_wait(B_RE, i & 1);
                wg_fence();
#pragma unroll
                for (int s = 0; s < 5; s++) {
                    wgmma_out64(oc, desc_lo(SM_X, 128) + s * 16, desc_lo(SM_W, 10240) + s * 128, s || i);
                    wgmma_out96(oc, desc_lo(SM_X, 128) + s * 16, desc_lo(SM_W, 10240) + 640 + s * 128, s || i);
                }
                wg_commit();
                wg_wait<0>();
                bar_sync(10, 128);
            }
#pragma unroll
            for (int t = 0; t < 40; t++) {
                const int col = (t < 32 ? kba * 64 + (t >> 1) * 8 : kbr * 64 + odd * 32 + ((t - 32) >> 1) * 8) + cq * 2;
                const uint32_t y = hfma2((t & 1) ? n1 : n0, nb[t], pack2(oc[2 * t], oc[2 * t + 1]));
                sts4(stg + cq * 4 + (t < 32 ? (t >> 4) * 2048 + (r + (t & 1) * 8) * 128 + ((((t >> 1) & 7) ^ r) << 4)
                                            : 4096 + (r + (t & 1) * 8) * 64 + ((((t - 32) >> 1) ^ (r >> 1)) << 4)), y);
                if (!((t & 1) ? rt1 : rt0)) *reinterpret_cast<uint32_t*>(P.op + ((orow + r + (t & 1) * 8) * 2 + par) * 640 + col) = y;
            }
            bar_sync(10, 128);
            if (leader) mbar_arrive(B_OE + 24);
        }
    }
}

typedef CUresult (*EncodeFn)(CUtensorMap*, CUtensorMapDataType, cuuint32_t, void*, const cuuint64_t*, const cuuint64_t*,
                             const cuuint32_t*, const cuuint32_t*, CUtensorMapInterleave, CUtensorMapSwizzle,
                             CUtensorMapL2promotion, CUtensorMapFloatOOBfill);

void encode(EncodeFn fn, CUtensorMap* m, const void* ptr, int rank, const cuuint64_t* dims, const cuuint64_t* strides,
            const cuuint32_t* box, CUtensorMapSwizzle swz,
            CUtensorMapL2promotion promo = CU_TENSOR_MAP_L2_PROMOTION_L2_128B) {
    const cuuint32_t es[4] = {1, 1, 1, 1};
    fn(m, CU_TENSOR_MAP_DATA_TYPE_BFLOAT16, rank, const_cast<void*>(ptr), dims, strides, box, es,
       CU_TENSOR_MAP_INTERLEAVE_NONE, swz, promo, CU_TENSOR_MAP_FLOAT_OOB_FILL_NONE);
}

}

extern "C" void kernel_launch(void* const* d_in, const int* in_sizes, int n_in, void* d_out, int out_size) {
    (void)in_sizes; (void)n_in; (void)out_size;
    Params P;
    P.xp = (const __nv_bfloat16*)d_in[0];
    for (int g = 0; g < 8; g++) {
        P.src[g] = 0;
        for (int i = 0; i < 8; i++) P.src[g] |= src_of(i, g) << i * 4;
    }
    P.upp = (const __nv_bfloat16*)d_in[6];
    P.op = (__nv_bfloat16*)d_out;
    P.w_r = (const __nv_bfloat16*)d_in[4];
    P.gate_w = (const __nv_bfloat16*)d_in[8];

    void* fp = nullptr;
    cudaDriverEntryPointQueryResult st;
    cudaGetDriverEntryPoint("cuTensorMapEncodeTiled", &fp, cudaEnableDefault, &st);
    EncodeFn fn = (EncodeFn)fp;
    const cuuint64_t xd[3] = {640, 2, 1024}, xs[2] = {1280, 2560};
    const cuuint32_t bx[3] = {64, 1, 64}, bx2[3] = {64, 1, 128};
    encode(fn, &P.x2, d_in[0], 3, xd, xs, bx2, CU_TENSOR_MAP_SWIZZLE_128B);
    encode(fn, &P.x, d_in[0], 3, xd, xs, bx, CU_TENSOR_MAP_SWIZZLE_128B);
    const cuuint64_t wd[3] = {640, 640, 3}, ws[2] = {3840, 1280};
    const cuuint32_t bw[3] = {64, 32, 3}, bwr[3] = {16, 32, 3};
    encode(fn, &P.w, d_in[1], 3, wd, ws, bw, CU_TENSOR_MAP_SWIZZLE_128B);
    encode(fn, &P.wr, d_in[1], 3, wd, ws, bwr, CU_TENSOR_MAP_SWIZZLE_32B);
    const cuuint64_t ad[3] = {64, 640, 10}, as[2] = {1280, 128}, bd[2] = {640, 640};
    const cuuint32_t ba[3] = {64, 80, 2}, bb[2] = {32, 80};
    encode(fn, &P.woa, d_in[2], 3, ad, as, ba, CU_TENSOR_MAP_SWIZZLE_128B, CU_TENSOR_MAP_L2_PROMOTION_NONE);
    encode(fn, &P.wob, d_in[2], 2, bd, as, bb, CU_TENSOR_MAP_SWIZZLE_128B, CU_TENSOR_MAP_L2_PROMOTION_NONE);
    const cuuint64_t gd[2] = {1728, 640}, gs[1] = {3456}, dd[3] = {64, 1728, 10};
    const cuuint32_t bg[2] = {64, 32}, bu[2] = {64, 48}, bdn[3] = {64, 64, 1}, bxg[3] = {64, 1, 16};
    encode(fn, &P.xg, d_in[0], 3, xd, xs, bxg, CU_TENSOR_MAP_SWIZZLE_128B);
    encode(fn, &P.gate, d_in[5], 2, gd, gs, bg, CU_TENSOR_MAP_SWIZZLE_128B);
    encode(fn, &P.up, d_in[6], 2, gd, gs, bg, CU_TENSOR_MAP_SWIZZLE_128B);
    encode(fn, &P.up2, d_in[6], 2, gd, gs, bu, CU_TENSOR_MAP_SWIZZLE_128B);
    encode(fn, &P.down, d_in[7], 3, dd, as, bdn, CU_TENSOR_MAP_SWIZZLE_128B);

    cudaFuncSetAttribute(fused_kernel, cudaFuncAttributeMaxDynamicSharedMemorySize, SM_TOTAL);
    fused_kernel<<<NCTA, 512, SM_TOTAL, cudaStreamPerThread>>>(P);
}
```

```cpp
#include <cuda_runtime.h>
#include <cuda_bf16.h>
#include <cuda.h>
#include <stdint.h>

namespace {

constexpr int NCTA = 128;
constexpr int NFFN = 108;
constexpr uint32_t SENT = 0xFFFFFFFFu;

constexpr uint32_t SB = 1024;
constexpr uint32_t SM_W = SB;
constexpr uint32_t SM_X = SB + 122880;
constexpr uint32_t SM_F = SB + 188416;
constexpr uint32_t SM_G = SB + 212992;
constexpr uint32_t SM_BAR = SB + 223232;
constexpr uint32_t SM_PROF = SB + 223744;
constexpr uint32_t SM_KEY = SB + 224000;
constexpr uint32_t SM_RED = SB + 224128;
constexpr uint32_t SM_XS = SB + 226688;
constexpr uint32_t SM_SENT = SB + 227328;
constexpr uint32_t SM_U = SM_RED + 1920;
constexpr uint32_t SM_GATE = SM_RED;
constexpr uint32_t SM_TOTAL = 232448;
constexpr uint32_t SM_HALO1 = SM_X + 30720;
constexpr uint32_t SM_HALO = SM_HALO1 + 12800;
constexpr uint32_t SM_UP = SM_W + 61440;
constexpr uint32_t SM_DN = SM_UP + 6144;
constexpr uint32_t SM_Y = SM_F + 26624;
constexpr uint32_t SM_OUT = SM_W + 92160;

constexpr uint32_t B_XL0 = SM_BAR, B_FULL = SM_BAR + 8, B_GT = SM_BAR + 72, B_RG = SM_BAR + 80, B_RG2 = SM_BAR + 88,
                   B_XS = SM_BAR + 96, B_EMPTY = SM_BAR + 128, B_DONE = SM_BAR + 192, B_XE = SM_BAR + 200,
                   B_GUD = SM_BAR + 224, B_OE = B_GUD + 8, B_OT = B_GUD + 40, B_MOD = B_GUD + 72,
                   B_GU = SM_BAR + 104, B_ALL = SM_BAR + 112, B_UP = SM_BAR + 120, B_DN = B_GUD + 80, B_RS = B_GUD + 88, B_INIT = B_GUD + 96,
                   B_RE = B_GUD + 104, B_G2 = B_GUD + 112, B_DD = B_GUD + 176, B_HF = B_GUD + 184;

struct Params {
    CUtensorMap x, x2, w, wr, woa, wob, xg, gate, up, up2, down;
    __nv_bfloat16* op;
    const __nv_bfloat16 *xp, *upp, *w_r, *gate_w;
    uint32_t src[8];
};

constexpr int SC_O = 0;
constexpr int SC_HALO = 1280;
constexpr int SC_GU = 1440;
constexpr int SC_Y = 1504;
constexpr int SC_SIZE = 1600;
__device__ __align__(128) uint4 g_sc[NCTA * SC_SIZE];
__device__ __align__(128) uint4 g_cand[NCTA];
__device__ __align__(16) uint32_t g_gate[2048];
__device__ __align__(128) unsigned g_cnt[64];
#define TSM(i) do { } while (0)
#define TS(i) do { } while (0)
#define TS2(i) do { } while (0)
#define TSX(i) do { } while (0)

__device__ __forceinline__ uint32_t smem_u32(const void* p) { return (uint32_t)__cvta_generic_to_shared(p); }
__device__ __forceinline__ void fault() { asm volatile("st.shared.u32 [%0], %0;" ::"r"(0x100001) : "memory"); }
__device__ __forceinline__ void mbar_init(uint32_t bar, uint32_t cnt) {
    asm volatile("mbarrier.init.shared::cta.b64 [%0], %1;" ::"r"(bar), "r"(cnt) : "memory");
}
__device__ __forceinline__ void mbar_expect_tx(uint32_t bar, uint32_t bytes) {
    asm volatile("mbarrier.arrive.expect_tx.shared::cta.b64 _, [%0], %1;" ::"r"(bar), "r"(bytes) : "memory");
}
__device__ __forceinline__ void mbar_arrive(uint32_t bar) {
    asm volatile("mbarrier.arrive.shared::cta.b64 _, [%0];" ::"r"(bar) : "memory");
}
__device__ __forceinline__ bool mbar_try(uint32_t bar, uint32_t parity) {
    uint32_t ok;
    asm volatile("{\n.reg .pred p;\nmbarrier.try_wait.parity.shared::cta.b64 p, [%1], %2;\nselp.u32 %0, 1, 0, p;\n}"
                 : "=r"(ok) : "r"(bar), "r"(parity) : "memory");
    return ok;
}
__device__ __forceinline__ void mbar_wait(uint32_t bar, uint32_t parity) {
    asm volatile("{\n.reg .pred p;\nAGAIN:\nmbarrier.try_wait.parity.shared::cta.b64 p, [%0], %1;\n@!p bra AGAIN;\n}"
                 ::"r"(bar), "r"(parity) : "memory");
}
__device__ __forceinline__ void tma_2d(uint32_t dst, const CUtensorMap* m, uint32_t bar, int c0, int c1) {
    asm volatile("cp.async.bulk.tensor.2d.shared::cluster.global.mbarrier::complete_tx::bytes [%0], [%1, {%3, %4}], [%2];"
                 ::"r"(dst), "l"(m), "r"(bar), "r"(c0), "r"(c1) : "memory");
}
__device__ __forceinline__ void bulk_load(uint32_t dst, const void* src, uint32_t bytes, uint32_t bar) {
    asm volatile("cp.async.bulk.shared::cluster.global.mbarrier::complete_tx::bytes [%0], [%1], %2, [%3];"
                 ::"r"(dst), "l"(src), "r"(bytes), "r"(bar) : "memory");
}
__device__ __forceinline__ void bulk_store(void* dst, uint32_t src, uint32_t bytes) {
    asm volatile("cp.async.bulk.global.shared::cta.bulk_group [%0], [%1], %2;" ::"l"(dst), "r"(src), "r"(bytes) : "memory");
}
__device__ __forceinline__ void tma_3d(uint32_t dst, const CUtensorMap* m, uint32_t bar, int c0, int c1, int c2) {
    asm volatile("cp.async.bulk.tensor.3d.shared::cluster.global.mbarrier::complete_tx::bytes [%0], [%1, {%3, %4, %5}], [%2];"
                 ::"r"(dst), "l"(m), "r"(bar), "r"(c0), "r"(c1), "r"(c2) : "memory");
}
__device__ __forceinline__ void fence_async_smem() { asm volatile("fence.proxy.async.shared::cta;" ::: "memory"); }
__device__ __forceinline__ void wg_fence() { asm volatile("wgmma.fence.sync.aligned;" ::: "memory"); }
__device__ __forceinline__ void wg_commit() { asm volatile("wgmma.commit_group.sync.aligned;" ::: "memory"); }
template <int N> __device__ __forceinline__ void wg_wait() { asm volatile("wgmma.wait_group.sync.aligned %0;" ::"n"(N) : "memory"); }
__device__ __forceinline__ void bar_sync(int id, int n) { asm volatile("bar.cta.sync %0, %1;" ::"r"(id), "r"(n) : "memory"); }
__device__ __forceinline__ void bar_arrive(int id, int n) { asm volatile("bar.cta.arrive %0, %1;" ::"r"(id), "r"(n) : "memory"); }

__device__ constexpr uint32_t desc_lo(uint32_t addr, uint32_t lbo) { return (addr >> 4) | ((lbo >> 4) << 16); }
__device__ __forceinline__ bool elect_one() {
    uint32_t p;
    asm volatile("{\n.reg .pred p;\nelect.sync _|p, 0xffffffff;\nselp.u32 %0, 1, 0, p;\n}" : "=r"(p));
    return p;
}
__device__ __forceinline__ uint32_t ld_relaxed4(const void* p) {
    uint32_t v;
    asm volatile("ld.relaxed.gpu.global.u32 %0, [%1];" : "=r"(v) : "l"(p) : "memory");
    return v;
}
__device__ __forceinline__ void st_relaxed4(void* p, uint32_t v) {
    asm volatile("st.relaxed.gpu.global.u32 [%0], %1;" ::"l"(p), "r"(v) : "memory");
}
__device__ __forceinline__ void red_inc(unsigned* p, unsigned after) {
    asm volatile("red.relaxed.gpu.global.add.u32 [%0], 1;" ::"l"(p), "r"(after) : "memory");
}
__device__ __forceinline__ uint32_t lds4(uint32_t a) {
    uint32_t v;
    asm volatile("ld.shared.u32 %0, [%1];" : "=r"(v) : "r"(a) : "memory");
    return v;
}
__device__ __forceinline__ void sts4(uint32_t a, uint32_t v) { asm volatile("st.shared.u32 [%0], %1;" ::"r"(a), "r"(v) : "memory"); }
__device__ __forceinline__ uint32_t hadd2(uint32_t a, uint32_t b) {
    uint32_t d;
    asm("add.rn.bf16x2 %0, %1, %2;" : "=r"(d) : "r"(a), "r"(b));
    return d;
}
__device__ __forceinline__ uint32_t hfma2(uint32_t a, uint32_t b, uint32_t c) {
    uint32_t d;
    asm("fma.rn.bf16x2 %0, %1, %2, %3;" : "=r"(d) : "r"(a), "r"(b), "r"(c));
    return d;
}
__device__ __forceinline__ uint4 ld_relaxed16(const void* p) {
    uint4 v;
    asm volatile("{\n.reg .b128 t;\n.reg .b64 lo, hi;\nld.relaxed.gpu.global.b128 t, [%4];\nmov.b128 {lo, hi}, t;\n"
                 "mov.b64 {%0, %1}, lo;\nmov.b64 {%2, %3}, hi;\n}" : "=r"(v.x), "=r"(v.y), "=r"(v.z), "=r"(v.w) : "l"(p) : "memory");
    return v;
}
__device__ __forceinline__ void st_relaxed16(void* p, uint32_t a, uint32_t b, uint32_t c, uint32_t d) {
    uint64_t lo = (uint64_t)a | ((uint64_t)b << 32), hi = (uint64_t)c | ((uint64_t)d << 32);
    asm volatile("{\n.reg .b128 t;\nmov.b128 t, {%1, %2};\nst.relaxed.gpu.global.b128 [%0], t;\n}" ::"l"(p), "l"(lo), "l"(hi) : "memory");
}
__device__ __forceinline__ uint4 lds16(uint32_t a) {
    uint4 v;
    asm volatile("ld.shared.v4.u32 {%0, %1, %2, %3}, [%4];" : "=r"(v.x), "=r"(v.y), "=r"(v.z), "=r"(v.w) : "r"(a) : "memory");
    return v;
}
__device__ __forceinline__ void sts16(uint32_t a, uint32_t x, uint32_t y, uint32_t z, uint32_t w) {
    asm volatile("st.shared.v4.u32 [%0], {%1, %2, %3, %4};" ::"r"(a), "r"(x), "r"(y), "r"(z), "r"(w) : "memory");
}
__device__ __forceinline__ uint32_t pack2(float lo, float hi) {
    uint32_t r;
    asm("cvt.rn.bf16x2.f32 %0, %1, %2;" : "=r"(r) : "f"(hi), "f"(lo));
    return r;
}
__device__ __forceinline__ uint32_t pack2v(float lo, float hi) {
    uint32_t r;
    asm volatile("cvt.rn.bf16x2.f32 %0, %1, %2;" : "=r"(r) : "f"(hi), "f"(lo));
    return r;
}
__device__ __forceinline__ uint32_t shl(uint32_t v, uint32_t n) {
    uint32_t r;
    asm("shl.b32 %0, %1, %2;" : "=r"(r) : "r"(v), "r"(n));
    return r;
}
__device__ __forceinline__ float bf_lo(uint32_t u) { return __uint_as_float(u << 16); }
__device__ __forceinline__ float bf_hi(uint32_t u) { return __uint_as_float(u & 0xFFFF0000u); }
__device__ __forceinline__ float bf_round(float f) { return __bfloat162float(__float2bfloat16_rn(f)); }
__device__ __forceinline__ uint32_t movm(uint32_t a) {
    uint32_t d;
    asm volatile("movmatrix.sync.aligned.m8n8.trans.b16 %0, %1;" : "=r"(d) : "r"(a));
    return d;
}
__device__ __forceinline__ void mma16(float (&c)[4], uint32_t a0, uint32_t a1, uint32_t a2, uint32_t a3, uint32_t b0, uint32_t b1) {
    asm volatile("mma.sync.aligned.m16n8k16.row.col.f32.bf16.bf16.f32 {%0,%1,%2,%3}, {%4,%5,%6,%7}, {%8,%9}, {%0,%1,%2,%3};"
                 : "+f"(c[0]), "+f"(c[1]), "+f"(c[2]), "+f"(c[3]) : "r"(a0), "r"(a1), "r"(a2), "r"(a3), "r"(b0), "r"(b1));
}
__device__ __forceinline__ void mma8(float (&c)[4], uint32_t a0, uint32_t a1, uint32_t b0) {
    asm volatile("mma.sync.aligned.m16n8k8.row.col.f32.bf16.bf16.f32 {%0,%1,%2,%3}, {%4,%5}, {%6}, {%0,%1,%2,%3};"
                 : "+f"(c[0]), "+f"(c[1]), "+f"(c[2]), "+f"(c[3]) : "r"(a0), "r"(a1), "r"(b0));
}
__device__ __forceinline__ float ex2(float x) { float y; asm("ex2.approx.ftz.f32 %0, %1;" : "=f"(y) : "f"(x)); return y; }
__device__ __forceinline__ float rcp(float x) { float y; asm("rcp.approx.ftz.f32 %0, %1;" : "=f"(y) : "f"(x)); return y; }
__device__ __forceinline__ float sigmoidf(float z) { return rcp(1.0f + ex2(z * -1.4426950408889634f)); }
__device__ __forceinline__ float u2f(uint32_t u) { return __uint_as_float(u); }
__device__ __forceinline__ uint32_t f2u(float f) { return __float_as_uint(f); }

__device__ __forceinline__ void wgmma_main(float (&d)[96], uint32_t a, uint32_t b, int scale_d) {
    asm volatile("{\n.reg .pred p;\n.reg .b64 da, db;\nsetp.ne.b32 p, %98, 0;\n"
        "mov.b64 da, {%96, 0x40000040};\nmov.b64 db, {%97, 0x40000040};\n"
        "wgmma.mma_async.sync.aligned.m64n192k16.f32.bf16.bf16 "
        "{%0, %1, %2, %3, %4, %5, %6, %7, %8, %9, %10, %11, %12, %13, %14, %15, "
        "%16, %17, %18, %19, %20, %21, %22, %23, %24, %25, %26, %27, %28, %29, %30, %31, "
        "%32, %33, %34, %35, %36, %37, %38, %39, %40, %41, %42, %43, %44, %45, %46, %47, "
        "%48, %49, %50, %51, %52, %53, %54, %55, %56, %57, %58, %59, %60, %61, %62, %63, "
        "%64, %65, %66, %67, %68, %69, %70, %71, %72, %73, %74, %75, %76, %77, %78, %79, "
        "%80, %81, %82, %83, %84, %85, %86, %87, %88, %89, %90, %91, %92, %93, %94, %95}, "
        "da, db, p, 1, 1, 0, 1;\n}\n"
        : "+f"(d[0]), "+f"(d[1]), "+f"(d[2]), "+f"(d[3]), "+f"(d[4]), "+f"(d[5]), "+f"(d[6]), "+f"(d[7]),
          "+f"(d[8]), "+f"(d[9]), "+f"(d[10]), "+f"(d[11]), "+f"(d[12]), "+f"(d[13]), "+f"(d[14]), "+f"(d[15]),
          "+f"(d[16]), "+f"(d[17]), "+f"(d[18]), "+f"(d[19]), "+f"(d[20]), "+f"(d[21]), "+f"(d[22]), "+f"(d[23]),
          "+f"(d[24]), "+f"(d[25]), "+f"(d[26]), "+f"(d[27]), "+f"(d[28]), "+f"(d[29]), "+f"(d[30]), "+f"(d[31]),
          "+f"(d[32]), "+f"(d[33]), "+f"(d[34]), "+f"(d[35]), "+f"(d[36]), "+f"(d[37]), "+f"(d[38]), "+f"(d[39]),
          "+f"(d[40]), "+f"(d[41]), "+f"(d[42]), "+f"(d[43]), "+f"(d[44]), "+f"(d[45]), "+f"(d[46]), "+f"(d[47]),
          "+f"(d[48]), "+f"(d[49]), "+f"(d[50]), "+f"(d[51]), "+f"(d[52]), "+f"(d[53]), "+f"(d[54]), "+f"(d[55]),
          "+f"(d[56]), "+f"(d[57]), "+f"(d[58]), "+f"(d[59]), "+f"(d[60]), "+f"(d[61]), "+f"(d[62]), "+f"(d[63]),
          "+f"(d[64]), "+f"(d[65]), "+f"(d[66]), "+f"(d[67]), "+f"(d[68]), "+f"(d[69]), "+f"(d[70]), "+f"(d[71]),
          "+f"(d[72]), "+f"(d[73]), "+f"(d[74]), "+f"(d[75]), "+f"(d[76]), "+f"(d[77]), "+f"(d[78]), "+f"(d[79]),
          "+f"(d[80]), "+f"(d[81]), "+f"(d[82]), "+f"(d[83]), "+f"(d[84]), "+f"(d[85]), "+f"(d[86]), "+f"(d[87]),
          "+f"(d[88]), "+f"(d[89]), "+f"(d[90]), "+f"(d[91]), "+f"(d[92]), "+f"(d[93]), "+f"(d[94]), "+f"(d[95])
        : "r"(a), "r"(b), "r"(scale_d));
}

__device__ __forceinline__ void wgmma_rem(float (&d)[24], uint32_t a, uint32_t b, int scale_d) {
    asm volatile("{\n.reg .pred p;\n.reg .b64 da, db;\nsetp.ne.b32 p, %26, 0;\n"
        "mov.b64 da, {%24, 0x40000040};\nmov.b64 db, {%25, 0xC0000010};\n"
        "wgmma.mma_async.sync.aligned.m64n48k16.f32.bf16.bf16 "
        "{%0, %1, %2, %3, %4, %5, %6, %7, %8, %9, %10, %11, %12, %13, %14, %15, "
        "%16, %17, %18, %19, %20, %21, %22, %23}, "
        "da, db, p, 1, 1, 0, 1;\n}\n"
        : "+f"(d[0]), "+f"(d[1]), "+f"(d[2]), "+f"(d[3]), "+f"(d[4]), "+f"(d[5]), "+f"(d[6]), "+f"(d[7]),
          "+f"(d[8]), "+f"(d[9]), "+f"(d[10]), "+f"(d[11]), "+f"(d[12]), "+f"(d[13]), "+f"(d[14]), "+f"(d[15]),
          "+f"(d[16]), "+f"(d[17]), "+f"(d[18]), "+f"(d[19]), "+f"(d[20]), "+f"(d[21]), "+f"(d[22]), "+f"(d[23])
        : "r"(a), "r"(b), "r"(scale_d));
}

__device__ __forceinline__ void wgmma_out64(float (&d)[80], uint32_t a, uint32_t b, int scale_d) {
    asm volatile("{\n.reg .pred p;\n.reg .b64 da, db;\nsetp.ne.b32 p, %34, 0;\n"
        "mov.b64 da, {%32, 0x50};\nmov.b64 db, {%33, 0x40000040};\n"
        "wgmma.mma_async.sync.aligned.m64n64k16.f32.bf16.bf16 "
        "{%0, %1, %2, %3, %4, %5, %6, %7, %8, %9, %10, %11, %12, %13, %14, %15, "
        "%16, %17, %18, %19, %20, %21, %22, %23, %24, %25, %26, %27, %28, %29, %30, %31}, "
        "da, db, p, 1, 1, 0, 1;\n}\n"
        : "+f"(d[0]), "+f"(d[1]), "+f"(d[2]), "+f"(d[3]), "+f"(d[4]), "+f"(d[5]), "+f"(d[6]), "+f"(d[7]),
          "+f"(d[8]), "+f"(d[9]), "+f"(d[10]), "+f"(d[11]), "+f"(d[12]), "+f"(d[13]), "+f"(d[14]), "+f"(d[15]),
          "+f"(d[16]), "+f"(d[17]), "+f"(d[18]), "+f"(d[19]), "+f"(d[20]), "+f"(d[21]), "+f"(d[22]), "+f"(d[23]),
          "+f"(d[24]), "+f"(d[25]), "+f"(d[26]), "+f"(d[27]), "+f"(d[28]), "+f"(d[29]), "+f"(d[30]), "+f"(d[31])
        : "r"(a), "r"(b), "r"(scale_d));
}
__device__ __forceinline__ void wgmma_out96(float (&d)[80], uint32_t a, uint32_t b, int scale_d) {
    asm volatile("{\n.reg .pred p;\n.reg .b64 da, db;\nsetp.ne.b32 p, %50, 0;\n"
        "mov.b64 da, {%48, 0x50};\nmov.b64 db, {%49, 0x40000040};\n"
        "wgmma.mma_async.sync.aligned.m64n96k16.f32.bf16.bf16 "
        "{%0, %1, %2, %3, %4, %5, %6, %7, %8, %9, %10, %11, %12, %13, %14, %15, "
        "%16, %17, %18, %19, %20, %21, %22, %23, %24, %25, %26, %27, %28, %29, %30, %31, "
        "%32, %33, %34, %35, %36, %37, %38, %39, %40, %41, %42, %43, %44, %45, %46, %47}, "
        "da, db, p, 1, 1, 0, 1;\n}\n"
        : "+f"(d[32]), "+f"(d[33]), "+f"(d[34]), "+f"(d[35]), "+f"(d[36]), "+f"(d[37]), "+f"(d[38]), "+f"(d[39]),
          "+f"(d[40]), "+f"(d[41]), "+f"(d[42]), "+f"(d[43]), "+f"(d[44]), "+f"(d[45]), "+f"(d[46]), "+f"(d[47]),
          "+f"(d[48]), "+f"(d[49]), "+f"(d[50]), "+f"(d[51]), "+f"(d[52]), "+f"(d[53]), "+f"(d[54]), "+f"(d[55]),
          "+f"(d[56]), "+f"(d[57]), "+f"(d[58]), "+f"(d[59]), "+f"(d[60]), "+f"(d[61]), "+f"(d[62]), "+f"(d[63]),
          "+f"(d[64]), "+f"(d[65]), "+f"(d[66]), "+f"(d[67]), "+f"(d[68]), "+f"(d[69]), "+f"(d[70]), "+f"(d[71]),
          "+f"(d[72]), "+f"(d[73]), "+f"(d[74]), "+f"(d[75]), "+f"(d[76]), "+f"(d[77]), "+f"(d[78]), "+f"(d[79])
        : "r"(a), "r"(b), "r"(scale_d));
}
__device__ __forceinline__ void wgmma_reg64(float (&d)[80], uint32_t a0, uint32_t a1, uint32_t a2, uint32_t a3, uint32_t b, int scale_d) {
    asm volatile("{\n.reg .pred p;\n.reg .b64 db;\nsetp.ne.b32 p, %37, 0;\nmov.b64 db, {%36, 0x40000040};\n"
        "wgmma.mma_async.sync.aligned.m64n64k16.f32.bf16.bf16 "
        "{%0, %1, %2, %3, %4, %5, %6, %7, %8, %9, %10, %11, %12, %13, %14, %15, "
        "%16, %17, %18, %19, %20, %21, %22, %23, %24, %25, %26, %27, %28, %29, %30, %31}, "
        "{%32, %33, %34, %35}, db, p, 1, 1, 1;\n}\n"
        : "+f"(d[0]), "+f"(d[1]), "+f"(d[2]), "+f"(d[3]), "+f"(d[4]), "+f"(d[5]), "+f"(d[6]), "+f"(d[7]),
          "+f"(d[8]), "+f"(d[9]), "+f"(d[10]), "+f"(d[11]), "+f"(d[12]), "+f"(d[13]), "+f"(d[14]), "+f"(d[15]),
          "+f"(d[16]), "+f"(d[17]), "+f"(d[18]), "+f"(d[19]), "+f"(d[20]), "+f"(d[21]), "+f"(d[22]), "+f"(d[23]),
          "+f"(d[24]), "+f"(d[25]), "+f"(d[26]), "+f"(d[27]), "+f"(d[28]), "+f"(d[29]), "+f"(d[30]), "+f"(d[31])
        : "r"(a0), "r"(a1), "r"(a2), "r"(a3), "r"(b), "r"(scale_d));
}
__device__ __forceinline__ void wgmma_reg96(float (&d)[80], uint32_t a0, uint32_t a1, uint32_t a2, uint32_t a3, uint32_t b, int scale_d) {
    asm volatile("{\n.reg .pred p;\n.reg .b64 db;\nsetp.ne.b32 p, %53, 0;\nmov.b64 db, {%52, 0x40000040};\n"
        "wgmma.mma_async.sync.aligned.m64n96k16.f32.bf16.bf16 "
        "{%0, %1, %2, %3, %4, %5, %6, %7, %8, %9, %10, %11, %12, %13, %14, %15, "
        "%16, %17, %18, %19, %20, %21, %22, %23, %24, %25, %26, %27, %28, %29, %30, %31, "
        "%32, %33, %34, %35, %36, %37, %38, %39, %40, %41, %42, %43, %44, %45, %46, %47}, "
        "{%48, %49, %50, %51}, db, p, 1, 1, 1;\n}\n"
        : "+f"(d[32]), "+f"(d[33]), "+f"(d[34]), "+f"(d[35]), "+f"(d[36]), "+f"(d[37]), "+f"(d[38]), "+f"(d[39]),
          "+f"(d[40]), "+f"(d[41]), "+f"(d[42]), "+f"(d[43]), "+f"(d[44]), "+f"(d[45]), "+f"(d[46]), "+f"(d[47]),
          "+f"(d[48]), "+f"(d[49]), "+f"(d[50]), "+f"(d[51]), "+f"(d[52]), "+f"(d[53]), "+f"(d[54]), "+f"(d[55]),
          "+f"(d[56]), "+f"(d[57]), "+f"(d[58]), "+f"(d[59]), "+f"(d[60]), "+f"(d[61]), "+f"(d[62]), "+f"(d[63]),
          "+f"(d[64]), "+f"(d[65]), "+f"(d[66]), "+f"(d[67]), "+f"(d[68]), "+f"(d[69]), "+f"(d[70]), "+f"(d[71]),
          "+f"(d[72]), "+f"(d[73]), "+f"(d[74]), "+f"(d[75]), "+f"(d[76]), "+f"(d[77]), "+f"(d[78]), "+f"(d[79])
        : "r"(a0), "r"(a1), "r"(a2), "r"(a3), "r"(b), "r"(scale_d));
}
__device__ __forceinline__ void wgmma_reg(float (&d)[80], uint32_t a0, uint32_t a1, uint32_t a2, uint32_t a3, uint32_t b, int scale_d) {
    wgmma_reg64(d, a0, a1, a2, a3, b, scale_d);
    wgmma_reg96(d, a0, a1, a2, a3, b + 640, scale_d);
}
#define TSQ(i) do { } while (0)
#define TSR(i) do { } while (0)
#define MAP_TILE(b) (((b) & 1) | (((b) >> 1) & 2) | (((b) >> 5) << 2))
#define MAP_HG(b) (((((b) >> 2) & 6) ^ (((b) & 32) ? 2 : 4)) | ((((b) >> 1) ^ ((b) >> 2) ^ ((b) >> 3) ^ ((b) >> 5) ^ 1) & 1))
#define SKEW 4
#define PACE 500
#define PACE_W0 (-600)
#define PACE_A 100
#define PACE_XA 25
#define T_SH 150
#define PACE_B 450
#define RG_T0 1700
#define RG_DT 200
#define GU_T0 3600
#define GU_DT 500
#define RS_T0 9200
#define RS_DT 200
#define HALO_D 250
#define PF_UP 7000
#define PF_DT 450
#define O_D 150
#define O_DT 300
#define C1_D 0
#define C2_D 0
#define C5_D 0
#define C6_D 100
#define C7_D 100
#define GH_DT 300
#define GX_D 400
#define Y_AT 1
#define CAND_T 8100
#define DN_D 0
#define GATE_T 9000
#define GH_T0 6800
#define NRS 2
#define DN0(q) ((q) * 3 - ((q) == 3))
#define WO_D ((uint64_t)(C1_D / 16) << 8 | (uint64_t)(C2_D / 16) * 0x10101 << 16 | (uint64_t)(C5_D / 16) << 40 | (uint64_t)(C6_D / 16) << 48 | (uint64_t)(C7_D / 16) << 56)

__device__ __forceinline__ unsigned block_id() { unsigned b; asm volatile("mov.u32 %0, %%ctaid.x;" : "=r"(b)); return b; }
__device__ __forceinline__ uint32_t keep(uint32_t v) { return __shfl_sync(0xffffffffu, v, threadIdx.x); }
__device__ __forceinline__ uint32_t ukeep(uint32_t v) { return __shfl_sync(0xffffffffu, v, 0); }
__device__ __forceinline__ void ldsm(uint32_t* d, uint32_t a) {
    asm volatile("ldmatrix.sync.aligned.m8n8.x4.shared.b16 {%0,%1,%2,%3}, [%4];"
                 : "=r"(d[0]), "=r"(d[1]), "=r"(d[2]), "=r"(d[3]) : "r"(a) : "memory");
}
__device__ __forceinline__ void stsm(uint32_t a, uint32_t x, uint32_t y, uint32_t z, uint32_t w) {
    asm volatile("stmatrix.sync.aligned.m8n8.x4.shared.b16 [%0], {%1,%2,%3,%4};" ::"r"(a), "r"(x), "r"(y), "r"(z), "r"(w) : "memory");
}
__device__ __forceinline__ void row_sums(float& sa, float& sb, float a0, float a1, float b0, float b1) {
    asm volatile("{\n.reg .f32 x, y;\nmma.sync.aligned.m16n8k8.row.col.f32.tf32.tf32.f32 {%0,x,%1,y}, {%2,%3,%4,%5}, {%6,%6}, {%7,%7,%7,%7};\n}"
                 : "=f"(sa), "=f"(sb) : "r"(f2u(a0)), "r"(f2u(b0)), "r"(f2u(a1)), "r"(f2u(b1)), "r"(0x3F800000), "f"(0.f));
}
template <bool SWP, int SEG, int E>
__device__ __forceinline__ void pack_blocks(uint32_t (&d)[10], const float (&am)[96], const float (&ar)[24]) {
#pragma unroll
    for (int t = 0; t < 10; t++) {
        const float* p = (SWP ? t < 2 : t >= 8) ? ar + (SEG * 2 + (t & 1)) * 4 + E : am + (SEG * 8 + t - (SWP ? 2 : 0)) * 4 + E;
        d[t] = pack2v(p[0], p[1]);
    }
}
#define HALF(hg) ((hg) >> 2)
#define CB(hg) ((hg) & 3)
constexpr int src_of(int i, int hg) {
    return i == 0 ? hg : (i - (i <= (hg | 4))) ^ (~hg & 4);
}

__device__ __forceinline__ uint32_t o_buf(int i) { return __byte_perm(0x5B000000u, 0x473D6F65u, i) << 10; }
__device__ constexpr uint32_t wo_buf(int i) { return SM_W + ((0x10546103u >> i * 4) & 7) * 30720; }

template <int N>
__device__ __forceinline__ void poll(uint4 (&a)[N], const uint4* p, int stride) {
    bool bad;
    do {
        bad = false;
#pragma unroll
        for (int s = 0; s < N; s++) a[s] = ld_relaxed16(p + s * stride);
#pragma unroll
        for (int s = 0; s < N; s++) bad |= a[s].w == SENT;
    } while (__any_sync(0xffffffffu, bad));
}
__device__ __forceinline__ void pace(unsigned t0, int t) {
    asm volatile("{\n.reg .pred p;\n.reg .s32 d;\nAGAIN:\nmov.u32 d, %%clock;\nsub.s32 d, d, %0;\nsetp.lt.s32 p, d, 0;\n"
                 "@p nanosleep.u32 20;\n@p bra AGAIN;\n}" ::"r"(t0 + t) : "memory");
}
__device__ __forceinline__ void l2_prefetch(const void* p) { asm volatile("prefetch.global.L2 [%0];" ::"l"(p) : "memory"); }

template <int ROW>
__device__ __forceinline__ void wgmma_vec(float (&d)[8], uint32_t a, uint32_t b, int scale_d) {
    asm volatile("{\n.reg .pred p;\n.reg .b64 da, db;\nsetp.ne.b32 p, %10, 0;\nmov.b64 da, {%8, 0x40000040};\nmov.b64 db, {%9, %11};\n"
                 "wgmma.mma_async.sync.aligned.m64n16k16.f32.bf16.bf16 {%0, %1, %2, %3, %4, %5, %6, %7}, da, db, p, 1, 1, 1, 0;\n}"
                 : "+f"(d[0]), "+f"(d[1]), "+f"(d[2]), "+f"(d[3]), "+f"(d[4]), "+f"(d[5]), "+f"(d[6]), "+f"(d[7])
                 : "r"(a), "r"(b), "r"(scale_d), "n"(ROW / 16));
}

__global__ void __launch_bounds__(512, 1) fused_kernel(const __grid_constant__ Params P) {
    extern __shared__ __align__(1024) uint8_t smem_raw[];
    const unsigned t_start = clock() - T_SH;
    const int tid = threadIdx.x, lane = tid & 31;
    const unsigned b0 = block_id();
    if (tid == 384) {
        const int tile = MAP_TILE(b0), hg = MAP_HG(b0), swp = (hg & 3) == 3;
        mbar_init(B_FULL, 1);
        asm volatile("fence.mbarrier_init.release.cluster;" ::: "memory");
        sts4(SM_PROF + 63 * 4, clock());
        tma_3d(SM_W, &P.w, B_FULL, hg * 80 + (swp ? 16 : 0), 0, 0);
        tma_3d(SM_X + 8192, &P.x, B_FULL, 0, tile & 1, (tile >> 1) * 128 + 64);
        tma_3d(SM_W + 12288, &P.wr, B_FULL, hg * 80 + (swp ? 0 : 64), 0, 0);
        mbar_init(B_XL0, 1);
        mbar_init(B_FULL + 8, 1);
        mbar_init(B_FULL + 16, 1);
        asm volatile("fence.mbarrier_init.release.cluster;" ::: "memory");
        tma_3d(SM_X, &P.x, B_XL0, 0, tile & 1, (tile >> 1) * 128);
        mbar_expect_tx(B_FULL, 15360 + 8192);
        mbar_expect_tx(B_XL0, 8192);
    }
    const int warp = __shfl_sync(0xffffffffu, tid >> 5, 0);
    if (warp < 8 && (warp & 3) && elect_one()) {
#pragma unroll
        for (int i = 0; i < 4; i++) mbar_init(SM_BAR + (warp - (warp >> 2)) * 32 + i * 8, warp < 4 ? 1 : warp < 7 ? 2 : 4);
        asm volatile("fence.mbarrier_init.release.cluster;" ::: "memory");
    }
    __syncthreads();
    const unsigned bx = block_id();
    const int tile = MAP_TILE(bx), hg = MAP_HG(bx);
    const int cid = tile * 8 + hg;
    const int par = tile & 1, p0 = (tile >> 1) * 128;
    uint4* const sc = g_sc + cid * SC_SIZE;
    const int fid = ((bx - 8) & 127) ^ (~bx >> 1 & 2);
    const bool swp = (hg & 3) == 3;
    const int wcm = hg * 80 + (swp ? 16 : 0), wcr = hg * 80 + (swp ? 0 : 64);
    if (warp == 12 && elect_one()) {
        mbar_expect_tx(B_FULL + 8, 15360);
        tma_3d(SM_W + 15360, &P.w, B_FULL + 8, wcm, 32, 0);
        tma_3d(SM_W + 15360 + 12288, &P.wr, B_FULL + 8, wcr, 32, 0);
        mbar_expect_tx(B_FULL + 16, 15360 + 16384);
        tma_3d(SM_W + 30720, &P.w, B_FULL + 16, wcm, 64, 0);
        tma_3d(SM_W + 30720 + 12288, &P.wr, B_FULL + 16, wcr, 64, 0);
    }

    if (warp >= 12) {
        asm volatile("setmaxnreg.dec.sync.aligned.u32 32;");
        if (warp == 12) {
            if (elect_one()) {
#pragma unroll 1
                for (int s = 3; s < 20; s++) {
                    const uint32_t fb = B_FULL + (s & 7) * 8, dst = SM_W + (s & 7) * 15360;
                    mbar_wait(fb + (B_EMPTY - B_FULL), ~(s >> 3) & 1);
                    pace(t_start, max(PACE_A + s * PACE_B, PACE_W0 + s * PACE));
                    mbar_expect_tx(fb, (s & 1) ? 15360 : 15360 + 16384);
                    tma_3d(dst, &P.w, fb, wcm, s * 32, 0);
                    tma_3d(dst + 12288, &P.wr, fb, wcr, s * 32, 0);
                    TS2(20 + s);
                }
                mbar_wait(B_RG2, 0);
                if (fid < NFFN) {
                    const int nd = 3 - (fid >> 1 & 1);
                    mbar_expect_tx(B_UP, 6144);
                    mbar_expect_tx(B_DN, nd * 8192);
                    mbar_wait(B_EMPTY + 4 * 8, 1);
                    TSQ(40);
                    tma_2d(SM_UP, &P.up2, B_UP, (fid >> 2) * 64, (fid & 3) * 160 + 112);
                    mbar_wait(B_EMPTY + 5 * 8, 1);
                    const unsigned t0 = clock();
#pragma unroll 1
                    for (int i = 0; i < nd; i++) {
                        pace(t0, i * DN_D);
                        tma_3d(SM_DN + i * 8192, &P.down, B_DN, 0, (fid >> 2) * 64, DN0(fid & 3) + i);
                    }
                    TSQ(41);
                }
                const int cb = CB(hg), ca = (cb * 5 + 1) >> 1, cr = cb * 160 + ((cb & 1) ? 0 : 128);
                unsigned t1 = 0;
#pragma unroll 1
                for (int j = 0; j < 8; j++) {
                    const int i = j ^ (j == 3 || j == 4 ? 7 : 0);
                    if (j != 3) mbar_wait(j < 3 ? B_EMPTY + ((2 * j + 7) & 7) * 8 : j == 5 ? B_HF : B_GUD + (j - 4) * 8, j == 0);
                    if (j != 3 && j != 4) t1 = clock();
                    pace(t1, (WO_D >> j * 8 & 255) * 16);
                    const uint32_t dst = wo_buf(i), gb = B_G2 + i * 8;
                    TSQ(20 + j);
                    mbar_expect_tx(gb, 25600);
                    tma_3d(dst, &P.woa, gb, 0, (P.src[hg] >> i * 4 & 7) * 80, ca);
                    tma_2d(dst + 20480, &P.wob, gb, cr, (P.src[hg] >> i * 4 & 7) * 80);
                }
            }
        } else if (warp == 14) {
            if (elect_one()) {
#pragma unroll 1
                for (int kb = 1; kb < 10; kb++) {
                    const uint32_t fb = B_FULL + (kb & 3) * 16, dst = SM_X + (kb & 3) * 16384;
                    mbar_wait(fb + (B_EMPTY - B_FULL + 8), ~(kb >> 2) & 1);
                    if (kb >= 4) mbar_wait(B_XE + (kb - 4 >> 1) * 8, 0);
                    pace(t_start, max(PACE_XA + 2 * kb * PACE_B, PACE_W0 - 50 + (2 * kb + 1) * PACE));
                    tma_3d(dst, &P.x2, fb, kb * 64, par, p0);
                }
            }
            __syncwarp();
            mbar_wait(B_ALL, 0);
            bar_sync(12, 64);
            pace(t_start, 0);
            pace(clock(), HALO_D);
            uint4 hv[5];
            poll<5>(hv, sc + (SC_HALO - (tile < 2 ? 0 : 16 * SC_SIZE) + lane), 32);
#pragma unroll
            for (int s = 0; s < 5; s++) sts16(SM_HALO + s * 512 + lane * 16, hv[s].x, hv[s].y, hv[s].z, hv[s].w);
            bar_arrive(8, 64);
            TSM(25);
        } else if (warp == 15) {
            int it = smem_u32(smem_raw) == SB ? 0 : 1 << 20;
            while (!mbar_try(B_XE + 16, 0))
                if (++it > (1 << 20)) fault();
            TSR(44);
            const uint32_t key = lds4(SM_KEY + (lane & 15) * 4), epoch = lds4(SM_KEY + 20 * 4);
            uint32_t k1 = __reduce_max_sync(0xffffffffu, key);
            uint32_t k2 = __reduce_max_sync(0xffffffffu, key == k1 ? 0u : key);
            if (elect_one()) {
                st_relaxed16(g_cand + cid, k1, k2, epoch, epoch);
                red_inc(g_cnt, epoch);
                TSR(45);
                if (fid < NFFN) {
                    mbar_expect_tx(B_GU, 10240);
                    pace(t_start, GH_T0);
                    tma_2d(SM_G, &P.up, B_GU, (fid >> 2) * 64, (fid & 3) * 160 + 32);
                    pace(clock(), GH_DT);
                    tma_2d(SM_G + 4096, &P.up2, B_GU, (fid >> 2) * 64, (fid & 3) * 160 + 64);
                }
            }
            __syncwarp();
            pace(t_start, CAND_T);
            TSR(46);
            uint4 cd[4];
            do {
                TSR(47);
#pragma unroll
                for (int j = 0; j < 4; j++) cd[j] = ld_relaxed16(g_cand + lane + 32 * j);
                if (++it > (1 << 20)) fault();
            } while (!__all_sync(0xffffffffu, cd[0].z == epoch && cd[1].z == epoch && cd[2].z == epoch && cd[3].z == epoch));
            TSR(48);
            uint32_t l1 = 0, l2 = 0;
#pragma unroll
            for (int j = 0; j < 4; j++) {
                l2 = max(max(l2, cd[j].y), min(l1, cd[j].x));
                l1 = max(l1, cd[j].x);
            }
            k1 = __reduce_max_sync(0xffffffffu, l1);
            k2 = __reduce_max_sync(0xffffffffu, l1 == k1 ? l2 : l1);
            if (elect_one()) {
                bulk_load(SM_XS, P.xp + (~k1 & 2047) * 640 + (fid & 3) * 160, 320, B_XS);
                bulk_load(SM_XS + 320, P.xp + (~k2 & 2047) * 640 + (fid & 3) * 160, 320, B_XS);
                sts16(SM_KEY + 16 * 4, k1, k2, 0, 0);
                mbar_expect_tx(B_XS, 640);
                mbar_arrive(B_ALL);
                TSR(49);
            }
            __syncwarp();
            while (!mbar_try(B_DONE, 0) || !mbar_try(B_MOD, 0))
                if (++it > (1 << 20)) fault();
        } else {
#pragma unroll 1
            for (int i = 0; i < 10; i++) sts16(SM_SENT + i * 512 + lane * 16, SENT, SENT, SENT, SENT);
            fence_async_smem();
            __syncwarp();
            if (elect_one()) {
                mbar_expect_tx(B_RG, 2560);
                asm volatile("mbarrier.expect_tx.relaxed.cta.shared::cta.b64 [%0], 10240;" ::"r"(B_RG2) : "memory");
                asm volatile("mbarrier.expect_tx.relaxed.cta.shared::cta.b64 [%0], 24576;" ::"r"(B_GU) : "memory");
                bulk_load(SM_RED, P.w_r, 1280, B_RG);
                bulk_load(SM_RED + 1280, P.gate_w, 1280, B_RG);
#pragma unroll
                for (int i = 0; i < 24; i++) mbar_init(B_GUD + i * 8, i == 23 ? 8 : i == 0 || i == 22 ? 4 : i < 15 + NRS ? 1 : 2);
#pragma unroll 1
                for (int i = 0; i < 5; i++) {
                    pace(t_start, RG_T0 + i * RG_DT);
                    tma_3d(SM_G + i * 2048, &P.xg, B_RG2, 320 + i * 64, par, p0 + hg * 16);
                }
                bulk_store(sc + SC_HALO, SM_SENT, 5120);
                asm volatile("cp.async.bulk.commit_group;\ncp.async.bulk.wait_group 0;" ::: "memory");
                mbar_arrive(B_RG2);
                TS(43);
#pragma unroll 1
                for (int i = 0; i < (fid < NFFN ? 6 : 0); i++) {
                    pace(t_start, GU_T0 + i * GU_DT);
                    tma_2d(SM_F + i * 4096, i < 5 ? &P.gate : &P.up, B_GU, (fid >> 2) * 64, (fid & 3) * 160 + (i < 5 ? i * 32 : 0));
                }
            }
            __syncwarp();
            if (fid < NFFN) {
                const __nv_bfloat16* up = P.upp + ((fid & 3) * 160 + 112 + lane) * 1728 + (fid >> 2) * 64;
                pace(t_start, PF_UP - PF_DT);
                l2_prefetch(up);
                l2_prefetch(up + 16 * 1728);
            }
            const unsigned goal = (ld_relaxed4(g_cnt + 32) | (NCTA - 1)) + 1;
            if (elect_one()) {
#pragma unroll 1
                for (int i = 0; i < 4; i++) {
                    pace(t_start, RS_T0 + i * RS_DT);
                    bulk_store(sc + i * 320, SM_SENT, 5120);
                }
                asm volatile("cp.async.bulk.commit_group;\ncp.async.bulk.wait_group 0;" ::: "memory");
                red_inc(g_cnt + 32, goal);
                mbar_arrive(B_RS);
            }
            __syncwarp();
            TSQ(30);
            while (ld_relaxed4(g_cnt + 32) - goal > 0x80000000u) {}
            if (lane == 0) mbar_arrive(B_INIT);
            TS(45);
        }
    } else if (warp >= 8) {
        asm volatile("setmaxnreg.dec.sync.aligned.u32 96;");
        const int t = tid - 256;
        const unsigned epoch = ld_relaxed4(g_cnt) / NCTA + 1;
        float gv = 0.f;
        int grow = hg * 16 + (t >> 3);
        {
            const uint32_t sw = (t >> 4) * 128 + (((t ^ (t >> 4)) & 7) << 4), hi = (t >> 3) & 1;
            const uint32_t xs = keep(sw + SM_X + hi * 16384 + hg * 2048), xg = keep(sw + SM_G + hi * 2048), ws = SM_RED + (t & 15) * 16;
            uint4 a[5], b[5], w[5];
            float r0 = 0.f, r1 = 0.f;
            auto load = [&](int p, uint32_t xa) { a[p] = lds16(xa); b[p] = lds16(xa + 1024); w[p] = lds16(ws + p * 256); };
            auto dot = [&](int p) {
                const uint32_t as[4] = {a[p].x, a[p].y, a[p].z, a[p].w}, bs[4] = {b[p].x, b[p].y, b[p].z, b[p].w};
                const uint32_t vs[4] = {w[p].x, w[p].y, w[p].z, w[p].w};
#pragma unroll
                for (int e = 0; e < 4; e++) {
                    r0 = fmaf(bf_lo(as[e]), bf_lo(vs[e]), r0);
                    r1 = fmaf(bf_lo(bs[e]), bf_lo(vs[e]), r1);
                    r0 = fmaf(bf_hi(as[e]), bf_hi(vs[e]), r0);
                    r1 = fmaf(bf_hi(bs[e]), bf_hi(vs[e]), r1);
                }
                asm volatile("" : "+f"(r0), "+f"(r1), "+r"(a[p].x), "+r"(a[p].y), "+r"(a[p].z), "+r"(a[p].w),
                                  "+r"(b[p].x), "+r"(b[p].y), "+r"(b[p].z), "+r"(b[p].w));
            };
            auto release = [&](int p) {
                if (__ballot_sync(0xffffffffu, lane == 0 || (a[p].w ^ w[p].w) == b[p].w) && lane == 0) mbar_arrive(B_XE + p * 8);
            };
            auto total = [&]() {
                float r = (hi ? r1 : r0) + __shfl_xor_sync(0xffffffffu, hi ? r0 : r1, 8);
                r += __shfl_xor_sync(0xffffffffu, r, 4);
                r += __shfl_xor_sync(0xffffffffu, r, 2);
                return bf_round(r + __shfl_xor_sync(0xffffffffu, r, 1));
            };
            mbar_wait(B_RG, 0);
            mbar_wait(B_XL0, 0);
            mbar_wait(B_FULL, 0);
            mbar_wait(B_FULL + 16, 0);
            TSR(32);
            load(0, xs);
            release(0);
            dot(0);
            TSR(33);
            mbar_wait(B_RG2, 0);
            TSR(34);
            load(3, xg + 2048);
            load(4, xg + 6144);
            mbar_wait(B_FULL + 32, 0);
            mbar_wait(B_FULL + 48, 0);
            TSR(35);
            load(1, xs + 32768);
            dot(3);
            release(1);
            dot(4);
            TSR(36);
            mbar_wait(B_FULL, 1);
            TSR(37);
            load(2, hi ? xg - 2048 : xs);
            dot(1);
            dot(2);
            TSR(42);
            grow = hg * 16 + (t >> 4) + hi * 8;
            const uint32_t u = f2u(total());
            sts4(SM_KEY + (t >> 3) * 4, (((int)u < 0 ? ~u : u | 0x80000000u) & 0xFFFF0000u) | (2047 - (p0 + grow) * 2 - par));
            sts4(SM_KEY + 20 * 4, epoch);
            __syncwarp();
            if (lane == 0) mbar_arrive(B_XE + 16);
            TSR(43);
            r0 = r1 = 0.f;
#pragma unroll
            for (int p = 0; p < 5; p++) w[p] = lds16(ws + 1280 + p * 256);
#pragma unroll
            for (int p = 0; p < 5; p++) dot(p);
            gv = total();
        }
        if ((lane & 7) == 4) st_relaxed4(g_gate + tile * 128 + grow, f2u(bf_round(sigmoidf(gv))) | (epoch & 0xFFFFu));
        TSR(38);
        if (warp == 9) {
            pace(t_start, GATE_T);
            uint4 v;
            do {
                asm volatile("ld.relaxed.gpu.global.v4.u32 {%0, %1, %2, %3}, [%4];"
                             : "=r"(v.x), "=r"(v.y), "=r"(v.z), "=r"(v.w) : "l"(g_gate + tile * 128 + lane * 4) : "memory");
            } while (__any_sync(0xffffffffu, ((v.x ^ epoch) | (v.y ^ epoch) | (v.z ^ epoch) | (v.w ^ epoch)) & 0xFFFFu));
            sts16(SM_GATE + lane * 16, v.x & 0xFFFF0000u, v.y & 0xFFFF0000u, v.z & 0xFFFF0000u, v.w & 0xFFFF0000u);
            __syncwarp();
            if (lane == 0) mbar_arrive(B_GT);
        }
        mbar_wait(B_XS, 0);
        TS(warp == 8 ? 50 : 63);
        TSR(50);
        const int cq = lane & 3, q = fid & 3;
        if (fid < NFFN) {
            uint4* const sc = g_sc + fid * SC_SIZE;
            float ga[8], ua[8];
            mbar_wait(B_GU, 0);
            TS(warp == 8 ? 61 : 63);
            mbar_wait(B_UP, 0);
            TSR(52);
            bar_sync(13, 256);
            TSM(warp == 8 ? 53 : 63);
            wg_fence();
#pragma unroll
            for (int i = 0; i < 10; i++) {
                wgmma_vec<320>(ga, desc_lo(SM_F, 16) + i * 128, desc_lo(SM_XS, 16) + i * 2, i);
                wgmma_vec<320>(ua, desc_lo(i < 7 ? SM_F + 20480 : SM_UP - 14336, 16) + i * 128, desc_lo(SM_XS, 16) + i * 2, i);
            }
            wg_commit();
            wg_wait<0>();
            TSM(warp == 8 ? 54 : 63);
            if (cq == 0) {
                st_relaxed16(sc + SC_GU + (t >> 2), f2u(ga[0]), f2u(ga[2]), f2u(ga[4]), f2u(ga[6]));
                st_relaxed16(sc + SC_GU + 32 + (t >> 2), f2u(ua[0]), f2u(ua[2]), f2u(ua[4]), f2u(ua[6]));
            }
            if (lane == 0) mbar_arrive(B_GUD);
            uint4 pq[2];
            pace(clock(), GX_D);
            poll<2>(pq, sc + (cq - q) * SC_SIZE + SC_GU + (t >> 2), 32);
            TSR(55);
            const bool tk = cq & 2, c8 = cq & 1;
            float v[4];
#pragma unroll
            for (int m = 0; m < 2; m++) {
                v[2 * m] = u2f(tk ? pq[m].z : pq[m].x) + __shfl_xor_sync(0xffffffffu, u2f(tk ? pq[m].x : pq[m].z), 2);
                v[2 * m + 1] = u2f(tk ? pq[m].w : pq[m].y) + __shfl_xor_sync(0xffffffffu, u2f(tk ? pq[m].y : pq[m].w), 2);
                v[m] = bf_round((c8 ? v[2 * m + 1] : v[2 * m]) + __shfl_xor_sync(0xffffffffu, c8 ? v[2 * m] : v[2 * m + 1], 1));
            }
            const uint32_t h = pack2(bf_round(v[0] * sigmoidf(v[0])) * v[1], 0.f);
            asm volatile("st.shared.u16 [%0], %1;" ::"r"(SM_XS + (cq >> 1) * 128 + ((t >> 5) * 16 + (cq & 1) * 8 + (lane >> 2)) * 2),
                         "h"((uint16_t)h) : "memory");
            fence_async_smem();
            bar_sync(4, 128);
            TS(warp == 8 ? 57 : 63);
            mbar_wait(B_DN, 0);
            bar_sync(14, 384);
            TSR(56);
            float y[3][8];
#pragma unroll 1
            for (int i = 0; i < 4; i++) {
                wg_fence();
#pragma unroll
                for (int m = 0; m < 3; m++)
                    wgmma_vec<128>(y[m], desc_lo(SM_DN + m * 8192, 16) + i * 128, desc_lo(SM_XS, 16) + i * 2, i);
                wg_commit();
            }
            wg_wait<0>();
            if (cq == 0) {
#pragma unroll
                for (int m = 0; m < 6; m++)
                    asm volatile("st.relaxed.gpu.global.v2.f32 [%0], {%1, %2};"
                                 ::"l"(reinterpret_cast<float2*>(sc + SC_Y) + (m & 1) * 96 + (m >> 1) * 32 + (t >> 2)),
                                   "f"(y[m >> 1][(m & 1) * 4]), "f"(y[m >> 1][(m & 1) * 4 + 2]) : "memory");
            }
        } else if (lane == 0) {
            mbar_arrive(B_GUD);
        }
        if (lane == 0) mbar_arrive(B_DD);
        TSM(warp == 8 ? 51 : 63);
        const uint32_t k1 = lds4(SM_KEY + 16 * 4), k2 = lds4(SM_KEY + 17 * 4);
        const uint32_t mine = (tile >> 1) * 256 + HALF(hg) * 128 + par;
        const bool own1 = (~k1 & 0x781) == mine, own2 = (~k2 & 0x781) == mine;
        if ((own1 || own2) && NFFN) {
            const int rg = min(t / 40, 2), c40 = t % 40, un = CB(hg) * 40 + c40, src = un < 48 ? 0 : un < 96 ? 1 : un < 128 ? 2 : 3;
            const int col = min(t >> 3, 9) * 16 + (t & 1) * 8 + (t & 6);
            mbar_wait(B_OE + Y_AT * 8, 0);
            TS(warp == 8 ? 60 : 63);
#pragma unroll 1
            for (int j = !own1; j <= own2; j++) {
                const uint4* p = g_sc + (rg * 4 + src) * SC_SIZE + SC_Y + j * 48 + un - DN0(src) * 16;
                const uint32_t key = j ? k2 : k1;
                const uint32_t xv = *reinterpret_cast<const uint32_t*>(P.xp + (~key & 2047) * 640 + CB(hg) * 160 + col);
                float y[4];
                bool bad;
                do {
                    uint4 yp[9];
#pragma unroll
                    for (int i = 0; i < 9; i++) yp[i] = ld_relaxed16(p + i * 12 * SC_SIZE);
                    y[0] = y[1] = y[2] = y[3] = 0.f;
                    bad = false;
#pragma unroll
                    for (int i = 0; i < 9; i++) {
                        y[0] += u2f(yp[i].x); y[1] += u2f(yp[i].y); y[2] += u2f(yp[i].z); y[3] += u2f(yp[i].w);
                        bad |= max(max(yp[i].x, yp[i].y), max(yp[i].z, yp[i].w)) == SENT;
                    }
                } while (__any_sync(0xffffffffu, bad));
                TS(warp == 8 ? 62 : 63);
                sts16(SM_Y + j * 2048 + t * 16, f2u(y[0]), f2u(y[1]), f2u(y[2]), f2u(y[3]));
                bar_sync(4, 128);
                if (t < 80) {
                    const uint32_t ya = SM_Y + j * 2048 + (t >> 1) * 16 + (t & 1) * 4;
                    const float rs = bf_round(sigmoidf(u2f(((int)key < 0 ? key & 0x7FFFFFFFu : ~key) & 0xFFFF0000u)));
                    const float y0 = u2f(lds4(ya)) + u2f(lds4(ya + 640)) + u2f(lds4(ya + 1280));
                    const float y1 = u2f(lds4(ya + 8)) + u2f(lds4(ya + 648)) + u2f(lds4(ya + 1288));
                    sts4(SM_U + j * 320 + t * 4, hadd2(xv, pack2(bf_round(y0) * rs, bf_round(y1) * rs)));
                }
            }
            const int cc = col + (CB(hg) & 1 ? (col < 32 ? 128 : -32) : 0);
            mbar_wait(B_GT, 0);
#pragma unroll 1
            for (int j = !own1; j <= own2; j++) {
                const uint32_t tk = ~(j ? k2 : k1) & 2047, rr = tk >> 1 & 15, stg = SM_OUT + (tk >> 5 & 3) * 5120;
                const float n = 1.f - u2f(lds4(SM_GATE + (tk & 254) * 2));
                uint32_t u = lds4(SM_U + j * 320 + t * 4), nn = pack2(n, n), ca = stg + rr * 128 + (rr & 7) * 16;
                uint32_t aa = stg + (cc & 6) * 2 + (cc < 128 ? (cc >> 6) * 2048 + rr * 128 + (((cc >> 3 ^ rr) & 7) << 4)
                                                             : 4096 + rr * 64 + (((cc >> 3 ^ rr >> 1) & 3) << 4));
                __nv_bfloat16* dst = P.op + tk * 640 + CB(hg) * 160 + col;
                asm volatile("" : "+r"(u), "+r"(nn), "+r"(ca), "+r"(aa), "+l"(dst));
                mbar_wait(B_DONE, 0);
                const float chk = u2f(lds4(ca));
                uint32_t a = lds4(aa);
                if (chk != chk) {
                    mbar_wait(B_OE + 24, 0);
                    a = lds4(aa);
                }
                if (t < 80) *reinterpret_cast<uint32_t*>(dst) = hfma2(nn, u, a);
            }
        }
        if (t == 0) mbar_arrive(B_MOD);
        TS(warp == 8 ? 52 : 63);
    } else {
        asm volatile("setmaxnreg.inc.sync.aligned.u32 192;");
        const int wg = warp >> 2;
        const bool leader = (tid & 127) == 0;
        bool rel = false;
        uint32_t nb[40];
        const int odd = CB(hg) & 1, kba = ukeep(wg == HALF(hg) ? (CB(hg) * 5 + 1) >> 1 : 16), kbr = ukeep(kba + 2 - odd * 3);
        const int kbs = wg ? -1 : (20 - SKEW) / 2;
        const uint32_t xrow = keep(SM_X + (warp * 16 + (lane & 15)) * 128 + (((lane >> 4) ^ (lane & 7)) << 4));
        const uint32_t xr4 = keep((xrow ^ odd * 64) + (kbr & 3) * 16384), xr5 = keep(xr4 ^ 32);
        uint32_t xq[8];
        const int klo = ukeep(kba - odd);
#pragma unroll
        for (int i = 0; i < 8; i++) xq[i] = keep((xrow ^ (i & 3) * 32) + ((kba + (i >> 2)) & 3) * 16384);
        const int w4 = warp & 3, r = lane >> 2, cq = lane & 3;
        float am[96], ar[24];
        TSM(warp == 0 ? 3 : 63);
        if (wg == 0) mbar_wait(B_XL0, 0);
#pragma unroll 1
        for (int kb = 0; kb < 10; kb++) {
            const uint32_t fb = B_FULL + (kb & 3) * 16, wo = (kb & 3) * 1920, ph = (kb >> 2) & 1;
            const uint32_t xo = desc_lo(SM_X, 16) + wg * 512 + (kb & 3) * 1024;
#pragma unroll
            for (int h = 0; h < 2; h++) {
                mbar_wait(fb + h * 8, ph);
                if (kb == 0 && h == 0) TS(warp == 0 ? 0 : warp == 4 ? 16 : 63);
                TS2(warp == 4 ? kb * 2 + h : 63);
                if (h == 1 && (unsigned)(kb - klo) < 3) {
                    if (kb == kba) { ldsm(nb, xq[0]); ldsm(nb + 4, xq[1]); ldsm(nb + 8, xq[2]); ldsm(nb + 12, xq[3]); }
                    else if (kb == kbr) { ldsm(nb + 32, xr4); ldsm(nb + 36, xr5); }
                    else { ldsm(nb + 16, xq[4]); ldsm(nb + 20, xq[5]); ldsm(nb + 24, xq[6]); ldsm(nb + 28, xq[7]); }
                }
                wg_wait<1>();
                if (rel) mbar_arrive(B_EMPTY + ((kb * 16 - 16) & 48) + h * 8);
                if (h == (SKEW & 1) && kb == kbs) bar_sync(5, 256);
                wg_fence();
                wgmma_main(am, xo + h * 4, desc_lo(SM_W + h * 15360, 4096) + wo, h || kb);
                wgmma_rem(ar, xo + h * 4, desc_lo(SM_W + h * 15360 + 12288, 1024) + wo, h || kb);
                wgmma_main(am, xo + h * 4 + 2, desc_lo(SM_W + h * 15360 + 2048, 4096) + wo, 1);
                wgmma_rem(ar, xo + h * 4 + 2, desc_lo(SM_W + h * 15360 + 12288 + 512, 1024) + wo, 1);
                wg_commit();
            }
            rel = leader;
        }
        if (wg == 1) bar_arrive(5, 256);
        if (wg == 0) bar_arrive(13, 256);
        mbar_wait(B_EMPTY + 7 * 8 - wg * 16, 1);
        wg_wait<0>();
        if (rel) mbar_arrive(B_EMPTY + 3 * 8);
        TSM(warp == 0 ? 2 : warp == 4 ? 18 : 63);

        uint32_t kl[10], kh[10], vl[10], vh[10], ql[10], qh[10], kp[10], vp[10];
        if (swp) {
            pack_blocks<true, 1, 2>(kh, am, ar);
            pack_blocks<true, 2, 2>(vh, am, ar);
        } else {
            pack_blocks<false, 1, 2>(kh, am, ar);
            pack_blocks<false, 2, 2>(vh, am, ar);
        }
        const uint32_t pbuf = (wg ? SM_HALO1 : SM_HALO) + w4 * 2560 + lane * 16;
        const uint32_t hbuf = warp == 3 ? SM_HALO1 + lane * 16 : pbuf + 2560;
        {
            const uint32_t ex[20] = {kh[0], kh[1], kh[3], kh[4], kh[5], kh[6], kh[8], kh[9], kh[2], kh[7],
                                     vh[0], vh[1], vh[2], vh[3], vh[4], vh[5], vh[6], vh[7], vh[8], vh[9]};
            if (warp == 7) {
                uint4* const hp = sc + SC_HALO + lane;
#pragma unroll
                for (int s = 0; s < 5; s++) st_relaxed16(hp + s * 32, ex[4 * s], ex[4 * s + 1], ex[4 * s + 2], ex[4 * s + 3]);
                bar_arrive(12, 64);
            } else {
#pragma unroll
                for (int s = 0; s < 5; s++) sts16(hbuf + s * 512, ex[4 * s], ex[4 * s + 1], ex[4 * s + 2], ex[4 * s + 3]);
            }
        }
        if (warp == 3) bar_arrive(11, 64);
        if (swp) {
            pack_blocks<true, 2, 0>(vl, am, ar);
            pack_blocks<true, 0, 0>(ql, am, ar);
            pack_blocks<true, 0, 2>(qh, am, ar);
            pack_blocks<true, 1, 0>(kl, am, ar);
        } else {
            pack_blocks<false, 2, 0>(vl, am, ar);
            pack_blocks<false, 0, 0>(ql, am, ar);
            pack_blocks<false, 0, 2>(qh, am, ar);
            pack_blocks<false, 1, 0>(kl, am, ar);
        }
#pragma unroll
        for (int t = 0; t < 10; t++) { vl[t] = movm(vl[t]); vh[t] = movm(vh[t]); }
        mbar_wait(B_RS, 0);
        mbar_wait(B_GT, 0);
        const float g0 = u2f(lds4(SM_GATE + warp * 64 + (lane & 28))), g1 = u2f(lds4(SM_GATE + 32 + warp * 64 + (lane & 28)));

        const bool no_prev = warp == 0 && tile < 2, low = cq < 2;
        const bool le0 = 2 * cq <= r, le1 = 2 * cq + 1 <= r;
        const uint32_t mle = (le0 ? 0xFFFFu : 0u) | (le1 ? 0xFFFF0000u : 0u);
        const float scl = 0.22360679774997896f * 1.4426950408889634f;
        uint32_t pl[4], ph[4], ol[10], oh[10], cl = 0;
        {
            float sl[4][4], sh[4][4], sp[4][4];
            bar_sync(6 + wg, 128);
            if (w4 == 0) bar_sync(8 + wg * 3, 64);
            {
                const uint4 a = lds16(pbuf), b = lds16(pbuf + 512), c = lds16(pbuf + 1024), d = lds16(pbuf + 1536), e = lds16(pbuf + 2048);
                kp[0] = a.x; kp[1] = a.y; kp[3] = a.z; kp[4] = a.w; kp[5] = b.x; kp[6] = b.y; kp[8] = b.z; kp[9] = b.w;
                kp[2] = c.x; kp[7] = c.y; vp[0] = c.z; vp[1] = c.w; vp[2] = d.x; vp[3] = d.y; vp[4] = d.z; vp[5] = d.w;
                vp[6] = e.x; vp[7] = e.y; vp[8] = e.z; vp[9] = e.w;
            }
#pragma unroll
            for (int h = 0; h < 4; h++) {
                const int ta = (h >> 1) * 5 + (h & 1) * 3, tc = (h >> 1) * 5 + 2;
                const uint32_t ml = low != (h & 1) ? ql[tc] : 0u, mh = low != (h & 1) ? qh[tc] : 0u;
#pragma unroll
                for (int e = 0; e < 4; e++) sl[h][e] = sh[h][e] = sp[h][e] = 0.f;
                mma16(sl[h], ql[ta], qh[ta], ql[ta + 1], qh[ta + 1], kl[ta], kl[ta + 1]);
                mma16(sh[h], ql[ta], qh[ta], ql[ta + 1], qh[ta + 1], kh[ta], kh[ta + 1]);
                mma8(sl[h], ml, mh, kl[tc]);
                mma8(sh[h], ml, mh, kh[tc]);
            }
#pragma unroll
            for (int h = 0; h < 4; h++) {
                const int ta = (h >> 1) * 5 + (h & 1) * 3, tc = (h >> 1) * 5 + 2;
                mma16(sp[h], ql[ta], qh[ta], ql[ta + 1], qh[ta + 1], kp[ta], kp[ta + 1]);
                mma8(sp[h], low != (h & 1) ? ql[tc] : 0u, low != (h & 1) ? qh[tc] : 0u, kp[tc]);
            }
#pragma unroll
            for (int t = 0; t < 10; t++) vp[t] = movm(vp[t]);
#pragma unroll
            for (int h = 0; h < 4; h++) {
                if (no_prev) sp[h][0] = sp[h][1] = -1e9f / 0.22360679774997896f;
                float a0 = le0 ? sl[h][0] : sp[h][0], a1 = le1 ? sl[h][1] : sp[h][1];
                float b0 = le0 ? sh[h][2] : sl[h][2], b1 = le1 ? sh[h][3] : sl[h][3];
                float ma = fmaxf(a0, a1), mb = fmaxf(b0, b1);
                ma = fmaxf(ma, __shfl_xor_sync(0xffffffffu, ma, 1));
                mb = fmaxf(mb, __shfl_xor_sync(0xffffffffu, mb, 1));
                ma = fmaxf(ma, __shfl_xor_sync(0xffffffffu, ma, 2));
                mb = fmaxf(mb, __shfl_xor_sync(0xffffffffu, mb, 2));
                ma *= -scl;
                mb *= -scl;
                a0 = ex2(fmaf(a0, scl, ma)), a1 = ex2(fmaf(a1, scl, ma));
                b0 = ex2(fmaf(b0, scl, mb)), b1 = ex2(fmaf(b1, scl, mb));
                row_sums(ma, mb, a0, a1, b0, b1);
                ma = rcp(ma) * g0;
                mb = rcp(mb) * g1;
                pl[h] = pack2(a0 * ma, a1 * ma);
                ph[h] = pack2(b0 * mb, b1 * mb);
            }
            uint32_t* const po = reinterpret_cast<uint32_t*>(sc + SC_O + warp * 160) + lane;
#pragma unroll
            for (int hp = 0; hp < 2; hp++) {
                float o[6][4];
#pragma unroll
                for (int h = 0; h < 2; h++) {
                    const int ta = hp * 5 + h * 3, tc = hp * 5 + 2;
                    const uint32_t a0 = pl[hp * 2 + h] & mle, a1 = ph[hp * 2 + h] & ~mle, a3 = ph[hp * 2 + h] & mle, ap = pl[hp * 2 + h] & ~mle;
#pragma unroll
                    for (int i = 0; i < 3; i++) o[h * 3 + i][0] = o[h * 3 + i][1] = o[h * 3 + i][2] = o[h * 3 + i][3] = 0.f;
#pragma unroll
                    for (int i = 0; i < 3; i++) mma8(o[h * 3 + i], a0, a1, vl[i < 2 ? ta + i : tc]);
#pragma unroll
                    for (int i = 0; i < 3; i++) mma16(o[h * 3 + i], ap, 0u, 0u, a3, vp[i < 2 ? ta + i : tc], vh[i < 2 ? ta + i : tc]);
                }
#pragma unroll
                for (int i = 0; i < 2; i++) {
                    ol[hp * 5 + i] = pack2(o[i][0], o[i][1]);
                    oh[hp * 5 + i] = pack2(o[i][2], o[i][3]);
                    ol[hp * 5 + 3 + i] = pack2(o[3 + i][0], o[3 + i][1]);
                    oh[hp * 5 + 3 + i] = pack2(o[3 + i][2], o[3 + i][3]);
                }
                ol[hp * 5 + 2] = pack2(low ? o[2][0] : o[5][0], low ? o[2][1] : o[5][1]);
                oh[hp * 5 + 2] = pack2(low ? o[2][2] : o[5][2], low ? o[2][3] : o[5][3]);
#pragma unroll
                for (int t = hp * 5; t < hp * 5 + 5; t++) {
                    st_relaxed4(po + t * 32, ol[t]);
                    st_relaxed4(po + t * 32 + 320, oh[t]);
                    if (t == 5) {
                        if (wg != HALF(hg)) bar_arrive(2, 256);
                        bar_arrive(14, 384);
                        if (lane == 0) mbar_arrive(B_HF);
                    }
                }
                if (!hp) cl = clock();
            }
        }
        TSM(warp == 0 ? 5 : warp == 4 ? 21 : warp == 5 ? 30 : warp == 1 ? 31 : warp == 2 ? 32 : warp == 3 ? 33 : warp == 6 ? 34 : 24);
        const uint4* ow = sc + (SC_O + HALF(hg) * 640 - hg * SC_SIZE);
        auto stage = [&]() {
            mbar_wait(B_INIT, 0);
            mbar_wait(B_OE, 0);
            const unsigned t0 = clock();
            uint32_t ph = 0;
#pragma unroll 1
            for (int i = w4 + 1 + NRS; i < 8; i += 4) {
                const uint4* src = ow + (P.src[hg] >> i * 4 & 7) * SC_SIZE;
                const uint32_t buf = o_buf(i), chk = buf + lane * 132;
                if (i >= 6) mbar_wait(B_DD, 0);
                pace(t0, (i - 3) * O_DT + O_D);
                uint32_t c;
                do {
                    if (elect_one()) {
                        mbar_expect_tx(B_OT + w4 * 8, 10240);
                        bulk_load(buf, src, 10240, B_OT + w4 * 8);
                    }
                    mbar_wait(B_OT + w4 * 8, ph);
                    if (i == 1 + NRS && !ph) TS(wg ? 19 : 20);
                    ph ^= 1;
                    c = max(max(lds4(chk), lds4(chk + 4096)), lds4(chk + 6144));
                } while (__any_sync(0xffffffffu, c == SENT));
                if (lane == 0) mbar_arrive(B_G2 + i * 8);
                TSM(32 + i);
            }
        };
        const bool idle = wg != HALF(hg);

        float oc[80];
        uint32_t routed = ~0u, n0, n1, stg, m128 = SM_SENT + lane * 16, m64 = m128, l128 = m128, l64 = m128, oa128, oa64;
        int orow;
        char *o128, *o64;
        bool nan;
        uint32_t c3 = 0;
        if (!idle || w4 == 3) {
        if (!idle) {
        uint32_t af[2][20];
        const uint32_t* const ap = reinterpret_cast<const uint32_t*>(ow + (~hg & 4) * SC_SIZE + w4 * 160) + lane;
        auto fetch = [&](int i) {
#pragma unroll
            for (int t = 0; t < 20; t++) af[i & 1][(t >> 1) + (t & 1) * 10] = ld_relaxed4(ap + i * SC_SIZE * 4 + ((t >> 1) + (t & 1) * 10) * 32);
        };
        auto missing = [&](int i, uint32_t c) {
            uint32_t m[3] = {af[i][0], af[i][1], ((uint32_t)clock() | c) >> 1};
#pragma unroll
            for (int t = 2; t < 20; t++) m[t / 2 % 3] = max(m[t / 2 % 3], af[i][t]);
            return __any_sync(0xffffffffu, max(max(m[0], m[1]), m[2]) == SENT);
        };
        auto addresses = [&](uint4 kv, uint32_t c2) {
            const uint32_t ln = lane + kv.z;
            orow = p0 + wg * 64 + w4 * 16;
            const uint32_t otok = orow * 2 + par, d1 = (~kv.x & 2047) - otok, d2 = (~kv.y & 2047) - otok;
            routed = (shl(~d1 & 1, d1 >> 1) | shl(~d2 & 1, d2 >> 1) | c2 << 16) & 0x7FFFFFFFu;
            n0 = routed >> r & 1 ? 0 : pack2(1.f - g0, 1.f - g0), n1 = routed >> r & 256 ? 0 : pack2(1.f - g1, 1.f - g1);
            stg = SM_OUT + w4 * 5120;
            m128 = stg + (ln & 15) * 128 + (((ln >> 4) ^ (ln & 7)) << 4);
            m64 = stg + 4096 + (ln & 15) * 64 + (((ln >> 4) ^ ((ln >> 1) & 3)) << 4);
            l128 = stg + (ln ^ (ln >> 3)) * 16;
            l64 = l128 + 4096;
            oa128 = otok * 1280 + kba * 128 + (ln >> 3) * (2560 - 128) + ln * 16;
            oa64 = otok * 1280 + kbr * 128 + odd * 64 + (ln >> 2) * (2560 - 64) + ln * 16;
            asm volatile("" : "+r"(n0), "+r"(n1), "+r"(routed), "+r"(m128), "+r"(m64), "+r"(l128), "+r"(oa128), "+r"(oa64));
            l64 = l128 + 4096;
        };
        auto step = [&](int i, int s) {
            wgmma_reg(oc, af[i][2 * s], af[i][10 + 2 * s], af[i][2 * s + 1], af[i][11 + 2 * s], desc_lo(wo_buf(i + 1), 10240) + s * 128, 1);
        };
        bar_sync(2, 256);
        mbar_wait(B_G2, 0);
        TSM(w4 == 0 ? 6 : 63);
        wg_fence();
#pragma unroll
        for (int s = 0; s < 5; s++)
            wgmma_reg(oc, ol[2 * s], oh[2 * s], ol[2 * s + 1], oh[2 * s + 1], desc_lo(wo_buf(0), 10240) + s * 128, s);
        wg_commit();
        mbar_wait(B_XS, 0);
        mbar_wait(B_INIT, 0);
        TSM(40 + w4);
        int nit = 0;
        const uint4 kv = lds16(SM_KEY + 64);
        fetch(0);
        uint32_t c1 = clock() | cl;
        wg_wait<0>();
        if (leader) mbar_arrive(B_OE);
        fetch(1);
        addresses(kv, clock());
        nit++;
        if (__builtin_expect(missing(0, c1), 0)) do {
            fetch(0);
            c1 = clock();
            fetch(1);
            nit++;
        } while (missing(0, c1));
        TSM(44 + w4);
        mbar_wait(B_G2 + 8, 0);
        TSM(w4 == 0 ? 7 : 63);
        wg_fence();
#pragma unroll
        for (int s = 0; s < 4; s++) step(0, s);
        const bool again = missing(1, 0);
        c1 = clock();
        step(0, 4);
        wg_commit();
        if (__builtin_expect(again, 0)) do fetch(1); while (missing(1, 0));
        TSM(56 + w4);
        mbar_wait(B_G2 + 16, 0);
        TSM(w4 == 0 ? 11 : 63);
        wg_fence();
#pragma unroll
        for (int s = 0; s < 5; s++) step(1, s);
        wg_commit();
        c3 = c1;
        wg_wait<1>();
        if (leader) mbar_arrive(B_OE + 8);
#pragma unroll 1
        for (int i = 3; i < 8; i++) {
            const uint32_t ao = desc_lo(0, 128) + (o_buf(i) >> 4), wo = desc_lo(0, 10240) + (wo_buf(i) >> 4);
            mbar_wait(B_G2 + i * 8, 0);
            TSM(w4 == 0 ? (i < 7 ? 9 + i : 17) : 63);
            wg_fence();
#pragma unroll
            for (int s = 0; s < 5; s++) wgmma_out64(oc, ao + s * 16, wo + s * 128, 1);
            wg_commit();
#pragma unroll
            for (int s = 0; s < 5; s++) wgmma_out96(oc, ao + s * 16, wo + 640 + s * 128, 1);
            wg_commit();
            if (i == 3) {
                wg_wait<2>();
                if (leader) mbar_arrive(B_OE + 16);
            }
        }
        o128 = reinterpret_cast<char*>(P.op) + oa128;
        o64 = reinterpret_cast<char*>(P.op) + oa64;
        TS(w4 == 0 ? 8 : 63);

        wg_wait<1>();
        TSM(w4 == 0 ? 9 : 63);
        }
        const bool rt0 = routed >> r & 1, rt1 = routed >> r & 256;
        uint4 v[3][4];
        auto get = [&](int part) {
#pragma unroll
            for (int i = 0; i < (part ? 4 : 2); i++)
                v[part][i] = lds16(!part ? l64 + i * 512 : (l128 ^ ((i & 1) * 64)) + i * 512 + (part * 4 - 4) * 512);
        };
        auto put = [&](int part) {
#pragma unroll
            for (int i = 0; i < (part ? 4 : 2); i++)
                if (!(part ? routed >> (lane >> 3) & 1 << 4 * i : i ? rt1 : rt0))
                    *reinterpret_cast<uint4*>(!part ? o64 + i * 8 * 2560 : o128 + i * 4 * 2560 + (part * 4 - 4) * 32) = v[part][i];
        };
#pragma unroll
        for (int pi = 0; pi < 3; pi++) {
            const int part = pi < 2 ? 1 - pi : pi;
            if (pi == 1) {
                c3 |= clock();
                wg_wait<0>();
            }
            const int s0 = part ? part * 4 - 4 : 8, ns = part ? 4 : 2;
#pragma unroll
            for (int i = 0; i < 4; i++) {
                if (i >= ns) break;
                const int s = s0 + i;
                const uint32_t y0 = hfma2(n0, nb[s * 4], pack2(oc[s * 8 + 0], oc[s * 8 + 1]));
                const uint32_t y1 = hfma2(n1, nb[s * 4 + 1], pack2(oc[s * 8 + 2], oc[s * 8 + 3]));
                const uint32_t y2 = hfma2(n0, nb[s * 4 + 2], pack2(oc[s * 8 + 4], oc[s * 8 + 5]));
                const uint32_t y3 = hfma2(n1, nb[s * 4 + 3], pack2(oc[s * 8 + 6], oc[s * 8 + 7]));
                if (s == 0) nan = u2f(y0) != u2f(y0) || u2f(y1) != u2f(y1);
                stsm(((s < 8 ? m128 : m64) ^ ((s & 3) * 32)) + (s & 4) * 512, y0, y1, y2, y3);
            }
            __syncwarp();
            if (pi == 2 && lane == 0 && (int)routed >= 0) mbar_arrive(B_DONE);
            get(part);
            put(part);
            if (pi == 0) TS(w4 == 0 ? 1 : 63);
        }
        TSM(w4 == 0 ? 10 : idle ? 62 : 63);
        }
        if (idle) {
            stage();
            return;
        }
        const bool rt0 = routed >> r & 1, rt1 = routed >> r & 256;
        uint32_t redo;
        asm volatile("{\n.reg .pred p, q;\nsetp.eq.u32 p, %1, 0xFFFFFFFF;\nbar.cta.red.or.pred q, 10, 128, p;\nselp.u32 %0, 1, 0, q;\n}"
                     : "=r"(redo) : "r"(nan ? SENT : c3 >> 1) : "memory");
        if (redo) {
            const int cb = CB(hg);
#pragma unroll 1
            for (int i = 0; i < 8; i++) {
                if (leader) {
                    mbar_expect_tx(B_RE, 25600);
                    tma_3d(SM_W, &P.woa, B_RE, 0, i * 80, (cb * 5 + 1) >> 1);
                    tma_2d(SM_W + 20480, &P.wob, B_RE, cb * 160 + ((cb & 1) ? 0 : 128), i * 80);
                }
#pragma unroll 1
                for (int s = 0; s < 20; s++) {
                    const int w = w4 * 640 + s * 32 + lane;
                    uint32_t v, it = 0;
                    do {
                        v = ld_relaxed4(reinterpret_cast<const uint32_t*>(ow + i * SC_SIZE) + w);
                        if (++it > (1u << 22)) fault();
                    } while ((v >> 16) == 0xFFFFu || (v & 0xFFFFu) == 0xFFFFu);
                    sts4(SM_X + w * 4, v);
                }
                fence_async_smem();
                __syncwarp();
                bar_sync(10, 128);
                mbar_wait(B_RE, i & 1);
                wg_fence();
#pragma unroll
                for (int s = 0; s < 5; s++) {
                    wgmma_out64(oc, desc_lo(SM_X, 128) + s * 16, desc_lo(SM_W, 10240) + s * 128, s || i);
                    wgmma_out96(oc, desc_lo(SM_X, 128) + s * 16, desc_lo(SM_W, 10240) + 640 + s * 128, s || i);
                }
                wg_commit();
                wg_wait<0>();
                bar_sync(10, 128);
            }
#pragma unroll
            for (int t = 0; t < 40; t++) {
                const int col = (t < 32 ? kba * 64 + (t >> 1) * 8 : kbr * 64 + odd * 32 + ((t - 32) >> 1) * 8) + cq * 2;
                const uint32_t y = hfma2((t & 1) ? n1 : n0, nb[t], pack2(oc[2 * t], oc[2 * t + 1]));
                sts4(stg + cq * 4 + (t < 32 ? (t >> 4) * 2048 + (r + (t & 1) * 8) * 128 + ((((t >> 1) & 7) ^ r) << 4)
                                            : 4096 + (r + (t & 1) * 8) * 64 + ((((t - 32) >> 1) ^ (r >> 1)) << 4)), y);
                if (!((t & 1) ? rt1 : rt0)) *reinterpret_cast<uint32_t*>(P.op + ((orow + r + (t & 1) * 8) * 2 + par) * 640 + col) = y;
            }
            bar_sync(10, 128);
            if (leader) mbar_arrive(B_OE + 24);
        }
    }
}

typedef CUresult (*EncodeFn)(CUtensorMap*, CUtensorMapDataType, cuuint32_t, void*, const cuuint64_t*, const cuuint64_t*,
                             const cuuint32_t*, const cuuint32_t*, CUtensorMapInterleave, CUtensorMapSwizzle,
                             CUtensorMapL2promotion, CUtensorMapFloatOOBfill);

void encode(EncodeFn fn, CUtensorMap* m, const void* ptr, int rank, const cuuint64_t* dims, const cuuint64_t* strides,
            const cuuint32_t* box, CUtensorMapSwizzle swz,
            CUtensorMapL2promotion promo = CU_TENSOR_MAP_L2_PROMOTION_L2_128B) {
    const cuuint32_t es[4] = {1, 1, 1, 1};
    fn(m, CU_TENSOR_MAP_DATA_TYPE_BFLOAT16, rank, const_cast<void*>(ptr), dims, strides, box, es,
       CU_TENSOR_MAP_INTERLEAVE_NONE, swz, promo, CU_TENSOR_MAP_FLOAT_OOB_FILL_NONE);
}

}

extern "C" void kernel_launch(void* const* d_in, const int* in_sizes, int n_in, void* d_out, int out_size) {
    (void)in_sizes; (void)n_in; (void)out_size;
    Params P;
    P.xp = (const __nv_bfloat16*)d_in[0];
    for (int g = 0; g < 8; g++) {
        P.src[g] = 0;
        for (int i = 0; i < 8; i++) P.src[g] |= src_of(i, g) << i * 4;
    }
    P.upp = (const __nv_bfloat16*)d_in[6];
    P.op = (__nv_bfloat16*)d_out;
    P.w_r = (const __nv_bfloat16*)d_in[4];
    P.gate_w = (const __nv_bfloat16*)d_in[8];

    void* fp = nullptr;
    cudaDriverEntryPointQueryResult st;
    cudaGetDriverEntryPoint("cuTensorMapEncodeTiled", &fp, cudaEnableDefault, &st);
    EncodeFn fn = (EncodeFn)fp;
    const cuuint64_t xd[3] = {640, 2, 1024}, xs[2] = {1280, 2560};
    const cuuint32_t bx[3] = {64, 1, 64}, bx2[3] = {64, 1, 128};
    encode(fn, &P.x2, d_in[0], 3, xd, xs, bx2, CU_TENSOR_MAP_SWIZZLE_128B);
    encode(fn, &P.x, d_in[0], 3, xd, xs, bx, CU_TENSOR_MAP_SWIZZLE_128B);
    const cuuint64_t wd[3] = {640, 640, 3}, ws[2] = {3840, 1280};
    const cuuint32_t bw[3] = {64, 32, 3}, bwr[3] = {16, 32, 3};
    encode(fn, &P.w, d_in[1], 3, wd, ws, bw, CU_TENSOR_MAP_SWIZZLE_128B);
    encode(fn, &P.wr, d_in[1], 3, wd, ws, bwr, CU_TENSOR_MAP_SWIZZLE_32B);
    const cuuint64_t ad[3] = {64, 640, 10}, as[2] = {1280, 128}, bd[2] = {640, 640};
    const cuuint32_t ba[3] = {64, 80, 2}, bb[2] = {32, 80};
    encode(fn, &P.woa, d_in[2], 3, ad, as, ba, CU_TENSOR_MAP_SWIZZLE_128B, CU_TENSOR_MAP_L2_PROMOTION_NONE);
    encode(fn, &P.wob, d_in[2], 2, bd, as, bb, CU_TENSOR_MAP_SWIZZLE_128B, CU_TENSOR_MAP_L2_PROMOTION_NONE);
    const cuuint64_t gd[2] = {1728, 640}, gs[1] = {3456}, dd[3] = {64, 1728, 10};
    const cuuint32_t bg[2] = {64, 32}, bu[2] = {64, 48}, bdn[3] = {64, 64, 1}, bxg[3] = {64, 1, 16};
    encode(fn, &P.xg, d_in[0], 3, xd, xs, bxg, CU_TENSOR_MAP_SWIZZLE_128B);
    encode(fn, &P.gate, d_in[5], 2, gd, gs, bg, CU_TENSOR_MAP_SWIZZLE_128B);
    encode(fn, &P.up, d_in[6], 2, gd, gs, bg, CU_TENSOR_MAP_SWIZZLE_128B);
    encode(fn, &P.up2, d_in[6], 2, gd, gs, bu, CU_TENSOR_MAP_SWIZZLE_128B);
    encode(fn, &P.down, d_in[7], 3, dd, as, bdn, CU_TENSOR_MAP_SWIZZLE_128B);

    cudaFuncSetAttribute(fused_kernel, cudaFuncAttributeMaxDynamicSharedMemorySize, SM_TOTAL);
    fused_kernel<<<NCTA, 512, SM_TOTAL, cudaStreamPerThread>>>(P);
}
```
